```python
import torch

def _softmax(x, axis=-1):
    return torch.softmax(x, dim=axis)
def _gelu(x):
    return torch.nn.functional.gelu(x, approximate="tanh")
def _silu(x):
    return torch.nn.functional.silu(x)
def _sigmoid(x):
    return torch.sigmoid(x)
def _layernorm(x, axis=-1, eps=1e-5):
    m = x.mean(dim=axis, keepdim=True)
    v = x.var(dim=axis, keepdim=True, unbiased=False)
    return (x - m) / torch.sqrt(v + eps)
def _scatter_add(tgt, idx, src, axis=0):
    return tgt.clone().index_add_(axis, idx, src)
def _segment_sum(src, seg, n):
    out = torch.zeros((n,) + src.shape[1:], dtype=src.dtype)
    return out.index_add_(0, seg, src)
def _pad(x, pw):
    flat = tuple(v for pair in reversed(pw) for v in pair)
    return torch.nn.functional.pad(x, flat)

kernel_name = 'parallel_sum__sliding_block_cached__dense_activation_mish__decode'

def setup_inputs():

    _w = (lambda a: (lambda t: t.to(torch.bfloat16) if t.is_floating_point() else t)(torch.as_tensor(a)))
    def _A_setup():
        B, Sq, D = 4, 1, 576
        Hq, Hkv, Sk, Dh = 32, 16, 4096, 128
        assert Hq % Hkv == 0, (Hq, Hkv)
        return {
            "x": _w((lambda *s: torch.randn(*s, dtype=torch.bfloat16) * 0.05)(B, Sq, D)),
            "k_cache": _w((lambda *s: torch.randn(*s, dtype=torch.bfloat16) * 1.6)(B, Hkv, Sk, Dh)),
            "v_cache": _w((lambda *s: torch.randn(*s, dtype=torch.bfloat16) * 0.4)(B, Hkv, Sk, Dh)),
            "wq": _w((lambda *s: torch.randn(*s, dtype=torch.bfloat16) * 1.6)(D, Hq * Dh) * (D ** -0.5)),
            "wo": _w((lambda *s: torch.randn(*s, dtype=torch.bfloat16) * 0.4)(Hq * Dh, D) * ((Hq * Dh) ** -0.5)),
        }
    _A_in = _A_setup()

    def _B_setup():
        B, S, D, F = 4, 1, 576, 4608
        return {
            "x": _w((lambda *s: torch.randn(*s, dtype=torch.bfloat16) * 0.05)(B, S, D)),
            "w1": _w((lambda *s: torch.randn(*s, dtype=torch.bfloat16) * 0.4)(D, F) * (D ** -0.5)),
            "b1": _w((lambda *s: torch.randn(*s, dtype=torch.bfloat16) * 0.2)(F)),
            "w2": _w((lambda *s: torch.randn(*s, dtype=torch.bfloat16) * 0.2)(F, D) * (F ** -0.5)),
        }
    _B_in = _B_setup()

    return {
        "A_x": _A_in["x"],
        "A_k_cache": _A_in["k_cache"],
        "A_v_cache": _A_in["v_cache"],
        "A_wq": _A_in["wq"],
        "A_wo": _A_in["wo"],
        "B_x": _B_in["x"],
        "B_w1": _B_in["w1"],
        "B_b1": _B_in["b1"],
        "B_w2": _B_in["w2"],
    }

def reference(A_x, A_k_cache, A_v_cache, A_wq, A_wo, B_x, B_w1, B_b1, B_w2):
    def _A_ref(x, k_cache, v_cache, wq, wo):
        B, Sq, D = x.shape
        Hq, Dh = 32, 128
        Hkv, Sk = k_cache.shape[1], k_cache.shape[2]
        W = min(4096, max(256, Sk // 4))
        rep = Hq // Hkv
        q = (lambda x, *d: x.permute(*d))((x @ wq).reshape(B, Sq, Hq, Dh), 0, 2, 1, 3)
        k = (lambda x, n, axis: torch.repeat_interleave(x, n, dim=axis))(k_cache[:, :, Sk - W:, :], rep, axis=1)
        v = (lambda x, n, axis: torch.repeat_interleave(x, n, dim=axis))(v_cache[:, :, Sk - W:, :], rep, axis=1)
        scores = torch.einsum("bhqd,bhkd->bhqk", q, k) * (Dh ** -0.5)
        p = _softmax(scores, axis=-1)
        o = torch.einsum("bhqk,bhkd->bhqd", p, v)
        return (lambda x, *d: x.permute(*d))(o, 0, 2, 1, 3).reshape(B, Sq, Hq * Dh) @ wo

    def _B_ref(x, w1, b1, w2):
        h = torch.einsum("bsd,df->bsf", x, w1) + b1
        sp = torch.log1p(torch.exp(-torch.abs(h))) + torch.where(h > 0, h, torch.zeros_like(h))
        act = h * torch.tanh(sp)
        return torch.einsum("bsf,fd->bsd", act, w2)

    x = A_x
    xn = _layernorm(x, axis=-1)
    return x + _A_ref(xn, A_k_cache, A_v_cache, A_wq, A_wo) + _B_ref(xn, B_w1, B_b1, B_w2)
```

```cpp
#include <cuda_runtime.h>
#include <cuda_bf16.h>
#include <cuda.h>
#include <stdint.h>

namespace {

constexpr int D_ = 576, HQ_ = 32, HKV_ = 16, SK_ = 4096, DH_ = 128, W_ = 1024, F_ = 4608, B_ = 4;
constexpr int NCTA = 128;
constexpr int PROD_WARP = 17;
constexpr int NTHREADS = 576;
#define DMIN 2
#define DMAX 6
#define PRATE 25.25f
#define PW0 26.f
#define PT0 700.f
#define DRYA 1
#define DRYB 1
#define DRYC 1
#define OWAIT (P_W2)
#define OREP 0
#define PFK 0
#define OSLEEP 200
#define FSLEEP 200
constexpr int SLOT = 16384;
constexpr int NSLOT = 13;
constexpr int P_WQ = 0, P_W1 = 3, P_K = 6, P_V = 14, P_W2 = 22, P_WO = 25, NPIECE = 29;
constexpr int NEMPTY = NPIECE - NSLOT;

constexpr int SM_RING = 0;
constexpr int SM_XN = NSLOT * SLOT;
constexpr int SM_ACT = SM_XN + 9 * 128;
constexpr int SM_O = SM_ACT + 9 * 128;
constexpr int SM_Q = SM_O + 8 * 128;
constexpr int SM_P = SM_Q + 8 * 128;
constexpr int SM_SC = SM_P + 32 * 128;
constexpr int SM_X = SM_SC + 512 * 8;
constexpr int SM_B1 = SM_X + 4 * 144 * 4;
constexpr int SM_HS = SM_B1 + 144 * 4;
constexpr int SM_RED = SM_HS + 4 * 144 * 4;
constexpr int SM_W = SM_RED + 32 * 4;
constexpr int SM_FULL = SM_W + 8;
constexpr int SM_EMPTY = SM_FULL + NPIECE * 8;
constexpr int SM_DONE = SM_EMPTY + NEMPTY * 8;
constexpr int SM_TAG = SM_DONE + 8;
constexpr int SM_TOTAL = SM_TAG + 16;
constexpr int SMEM_BYTES = SM_TOTAL + 1024;

constexpr unsigned SPIN_LIMIT = 1u << 21;

constexpr int BAR_CMP = 1;
constexpr int BAR_Q = 2;
constexpr int BAR_ACT = 3;
constexpr int BAR_O = 4;
constexpr int BAR_INIT = 5;
constexpr int BAR_G = 6;
constexpr int BAR_W = 7;

constexpr int G_QP = 0;
constexpr int G_HP = G_QP + HQ_ * 4 * B_ * DH_;
constexpr int G_OP = G_HP + 32 * 4 * B_ * 144;
constexpr int G_ST = G_OP + HQ_ * B_ * 2 * DH_;
constexpr int G_FP = G_ST + HKV_ * B_ * 2 * 8;
constexpr int G_EPOCH = G_FP + 4 * 32 * B_ * 144;
__device__ __align__(256) uint32_t g_x[G_EPOCH + 64];

#define TS(idx) do {} while (0)
#define TSA(idx) do {} while (0)
#define TSG(idx) do {} while (0)

__device__ __forceinline__ uint32_t smem_u32(const void* p) { return (uint32_t)__cvta_generic_to_shared(p); }
__device__ __forceinline__ void mbar_init(uint32_t bar, uint32_t cnt) {
    asm volatile("mbarrier.init.shared::cta.b64 [%0], %1;" ::"r"(bar), "r"(cnt) : "memory");
}
__device__ __forceinline__ void mbar_expect_tx(uint32_t bar, uint32_t bytes) {
    asm volatile("mbarrier.arrive.expect_tx.shared::cta.b64 _, [%0], %1;" ::"r"(bar), "r"(bytes) : "memory");
}
__device__ __forceinline__ void mbar_arrive(uint32_t bar) {
    asm volatile("mbarrier.arrive.shared::cta.b64 _, [%0];" ::"r"(bar) : "memory");
}
__device__ __forceinline__ bool mbar_test(uint32_t bar) {
    uint32_t ok;
    asm volatile(
        "{\n.reg .pred p;\n"
        "mbarrier.test_wait.parity.shared::cta.b64 p, [%1], 0;\n"
        "selp.u32 %0, 1, 0, p;\n}"
        : "=r"(ok) : "r"(bar) : "memory");
    return ok != 0;
}
__device__ __forceinline__ void mbar_wait(uint32_t bar) {
    asm volatile(
        "{\n.reg .pred p;\n.reg .u32 c;\n"
        "mov.u32 c, 0;\n"
        "W_%=:\n"
        "mbarrier.try_wait.parity.shared::cta.b64 p, [%0], 0;\n"
        "@p bra D_%=;\n"
        "add.u32 c, c, 1;\n"
        "setp.lt.u32 p, c, %1;\n"
        "@p bra W_%=;\n"
        "D_%=:\n}"
        ::"r"(bar), "n"(SPIN_LIMIT) : "memory");
}
__device__ __forceinline__ void tma_3d(uint32_t dst, const CUtensorMap* tm, int c0, int c1, int c2, uint32_t bar) {
    uint64_t pol;
    asm volatile("createpolicy.fractional.L2::evict_first.b64 %0, 1.0;" : "=l"(pol));
    asm volatile(
        "cp.async.bulk.tensor.3d.shared::cluster.global.mbarrier::complete_tx::bytes.L2::cache_hint"
        " [%0], [%1, {%3, %4, %5}], [%2], %6;"
        ::"r"(dst), "l"(tm), "r"(bar), "r"(c0), "r"(c1), "r"(c2), "l"(pol) : "memory");
}
__device__ __forceinline__ void prefetch_tm(const CUtensorMap* tm) {
    asm volatile("prefetch.tensormap [%0];" ::"l"(tm) : "memory");
}
__device__ __forceinline__ void ldsm_x4(uint32_t addr, uint32_t& r0, uint32_t& r1, uint32_t& r2, uint32_t& r3) {
    asm volatile("ldmatrix.sync.aligned.m8n8.x4.shared.b16 {%0,%1,%2,%3}, [%4];"
                 : "=r"(r0), "=r"(r1), "=r"(r2), "=r"(r3) : "r"(addr) : "memory");
}
__device__ __forceinline__ void ldsm_x4_t(uint32_t addr, uint32_t& r0, uint32_t& r1, uint32_t& r2, uint32_t& r3) {
    asm volatile("ldmatrix.sync.aligned.m8n8.x4.trans.shared.b16 {%0,%1,%2,%3}, [%4];"
                 : "=r"(r0), "=r"(r1), "=r"(r2), "=r"(r3) : "r"(addr) : "memory");
}
__device__ __forceinline__ void mma16816(float (&c)[4], uint32_t a0, uint32_t a1, uint32_t a2, uint32_t a3,
                                         uint32_t b0, uint32_t b1) {
    asm volatile(
        "mma.sync.aligned.m16n8k16.row.col.f32.bf16.bf16.f32 {%0,%1,%2,%3}, {%4,%5,%6,%7}, {%8,%9}, {%0,%1,%2,%3};"
        : "+f"(c[0]), "+f"(c[1]), "+f"(c[2]), "+f"(c[3])
        : "r"(a0), "r"(a1), "r"(a2), "r"(a3), "r"(b0), "r"(b1));
}
__device__ __forceinline__ void bar_sync(int id, int nthreads) {
    asm volatile("bar.sync %0, %1;" ::"r"(id), "r"(nthreads) : "memory");
}
__device__ __forceinline__ void bar_arrive(int id, int nthreads) {
    asm volatile("bar.arrive %0, %1;" ::"r"(id), "r"(nthreads) : "memory");
}
__device__ __forceinline__ uint2 lds64(uint32_t a) {
    uint2 v; asm volatile("ld.shared.v2.u32 {%0,%1}, [%2];" : "=r"(v.x), "=r"(v.y) : "r"(a) : "memory"); return v;
}
__device__ __forceinline__ float ldsf(uint32_t a) {
    float v; asm volatile("ld.shared.f32 %0, [%1];" : "=f"(v) : "r"(a) : "memory"); return v;
}
__device__ __forceinline__ void sts32(uint32_t a, uint32_t v) {
    asm volatile("st.shared.u32 [%0], %1;" ::"r"(a), "r"(v) : "memory");
}
__device__ __forceinline__ void stsf(uint32_t a, float v) {
    asm volatile("st.shared.f32 [%0], %1;" ::"r"(a), "f"(v) : "memory");
}
__device__ __forceinline__ void sts64f(uint32_t a, float v0, float v1) {
    asm volatile("st.shared.v2.f32 [%0], {%1,%2};" ::"r"(a), "f"(v0), "f"(v1) : "memory");
}
__device__ __forceinline__ void sts16(uint32_t a, __nv_bfloat16 v) {
    asm volatile("st.shared.u16 [%0], %1;" ::"r"(a), "h"(__bfloat16_as_ushort(v)) : "memory");
}
__device__ __forceinline__ uint32_t tagw(float v, uint32_t tag) { return (__float_as_uint(v) & ~15u) | tag; }
__device__ __forceinline__ void st_pub(uint32_t* p, uint32_t v) {
    asm volatile("st.relaxed.gpu.global.u32 [%0], %1;" ::"l"(p), "r"(v) : "memory");
}
__device__ __forceinline__ void st_pub4(uint32_t* d0, int S, uint32_t w0, uint32_t w1, uint32_t w2, uint32_t w3) {
    st_pub(d0, w0); st_pub(d0 + S, w1); st_pub(d0 + 8, w2); st_pub(d0 + S + 8, w3);
}
__device__ __forceinline__ uint4 ld_poll(const uint32_t* p) {
    uint4 v;
    asm volatile("ld.relaxed.gpu.global.v4.u32 {%0,%1,%2,%3}, [%4];"
                 : "=r"(v.x), "=r"(v.y), "=r"(v.z), "=r"(v.w) : "l"(p) : "memory");
    return v;
}
__device__ __forceinline__ bool tag_ok(const uint4& v, uint32_t tag) {
    return ((((v.x ^ tag) | (v.y ^ tag)) | ((v.z ^ tag) | (v.w ^ tag))) & 15u) == 0;
}
template <int N>
__device__ __forceinline__ void gather_n(const uint32_t* const (&p)[N], uint4 (&v)[N], uint32_t tag, bool rep,
                                         unsigned sleep_ns, int ts = -1) {
#pragma unroll
    for (int n = 0; n < N; n++) v[n] = make_uint4(0, 0, 0, 0);
    unsigned it = 0;
    if (ts >= 0) TS(ts);
    if (rep) {
#pragma unroll 1
        while (true) {
            v[0] = ld_poll(p[0]);
            if (tag_ok(v[0], tag) || ++it > SPIN_LIMIT) break;
            __nanosleep(sleep_ns);
        }
    }
    __syncwarp();
    if (ts >= 0) TS(ts + 1);
#pragma unroll 1
    while (true) {
#pragma unroll
        for (int n = 0; n < N; n++)
            if (!tag_ok(v[n], tag)) v[n] = ld_poll(p[n]);
        bool ok = true;
#pragma unroll
        for (int n = 0; n < N; n++) ok = ok && tag_ok(v[n], tag);
        if (ok || ++it > SPIN_LIMIT) break;
        __nanosleep(sleep_ns);
    }
    __syncwarp();
    if (ts >= 0) TS(ts + 2);
}
__device__ __forceinline__ float untag(uint32_t w) { return __uint_as_float(w & ~15u); }
__device__ __forceinline__ float bf16r(float v) { return __bfloat162float(__float2bfloat16_rn(v)); }
__device__ __forceinline__ uint32_t pack_bf16(float lo, float hi) {
    __nv_bfloat162 h = __floats2bfloat162_rn(lo, hi);
    return *reinterpret_cast<uint32_t*>(&h);
}
__device__ __forceinline__ uint32_t bv_off(int e2, int n) {
    return ((e2 >> 3) * 32 + n * 8 + (e2 & 3) * 2 + ((e2 >> 2) & 1)) * 4;
}
__device__ __forceinline__ float mish(float h) {
    const float e = __expf(fminf(h, 30.f));
    const float n = e * (e + 2.f);
    return h * __fdividef(n, n + 2.f);
}
__device__ __forceinline__ int slot_of(int p) { return p < NSLOT ? p : (p < 2 * NSLOT ? p - NSLOT : p - 2 * NSLOT); }

struct Maps { CUtensorMap m[6]; };

__global__ void __launch_bounds__(NTHREADS, 1)
fused_decode_kernel(const __grid_constant__ Maps maps, const __nv_bfloat16* __restrict__ x,
                    const __nv_bfloat16* __restrict__ b1, __nv_bfloat16* __restrict__ out,
                    const __nv_bfloat16* __restrict__ kc) {
    extern __shared__ unsigned char smem_raw[];
    const uint32_t sb = (smem_u32(smem_raw) + 1023u) & ~1023u;

    const int tid = threadIdx.x, warp = tid >> 5, lane = tid & 31;
    const int cta = blockIdx.x;
    const int ci = cta >> 2, cg = cta & 3;
    const int hkv = ci >> 1;
    const int bs = ((ci & 1) << 2) | cg;
    const int ab = bs >> 1, asplit = bs & 1;
    const int kv_row0 = (ab * HKV_ + hkv) * SK_ + (SK_ - W_) + asplit * 512;

    unsigned t_start = 0;
    if (tid == PROD_WARP * 32) {
        TSA(0);
#pragma unroll
        for (int p = 0; p < 4; p++) mbar_init(sb + SM_FULL + p * 8, 1);
        asm volatile("fence.mbarrier_init.release.cluster;" ::: "memory");
#pragma unroll
        for (int p = 0; p < 3; p++) {
            mbar_expect_tx(sb + SM_FULL + p * 8, 48 * 256);
            tma_3d(sb + p * SLOT, &maps.m[0], 0, cg * 144 + p * 48, 2 * ci, sb + SM_FULL + p * 8);
        }
        mbar_expect_tx(sb + SM_FULL + 3 * 8, 48 * 288);
        tma_3d(sb + 3 * SLOT, &maps.m[3], ci * 144, cg * 144, 0, sb + SM_FULL + 3 * 8);
        asm volatile("mov.u32 %0, %%globaltimer_lo;" : "=r"(t_start));
        TSA(1);
    }

    if (warp == PROD_WARP) {
        const int p = lane;
        int mi, c0 = 0, c1, bytes = 48 * 288;
        float kb;
        if (p < P_K)       { mi = 3; c0 = ci * 144; c1 = cg * 144 + (p - P_W1) * 48; kb = 36.f + 13.5f * (p - P_W1); }
        else if (p < P_V)  { mi = 1; c1 = kv_row0 + (p - P_K) * 64; bytes = 16384; kb = 76.5f + 16.f * (p - P_K); }
        else if (p < P_W2) { mi = 2; c1 = kv_row0 + (p - P_V) * 64; bytes = 16384; kb = 76.5f + 16.f * (p - P_K); }
        else if (p < P_WO) { mi = 4; c0 = cg * 144; c1 = ci * 144 + (p - P_W2) * 48; kb = 332.5f + 13.5f * (p - P_W2); }
        else { mi = 5; c0 = cg * 144; c1 = ci * 128 + (p - P_WO) * 32; bytes = 32 * 288; kb = 373.f + 9.f * (p - P_WO); }
        const uint32_t fb = sb + SM_FULL + p * 8;
        if (p >= 1 && p < 6) prefetch_tm(&maps.m[p]);
        if (lane == 0) {
#pragma unroll
            for (int q = 4; q < NPIECE; q++) mbar_init(sb + SM_FULL + q * 8, 1);
#pragma unroll
            for (int e = 0; e <= NEMPTY; e++) mbar_init(sb + SM_EMPTY + e * 8, (e == NEMPTY || (e >= P_W1 && e < P_W1 + 3)) ? 9 : 8);
            asm volatile("fence.mbarrier_init.release.cluster;" ::: "memory");
        }
        __syncwarp();
        bar_arrive(BAR_INIT, NTHREADS);
        if (p >= P_K) kb -= 16.f * min(p - P_K + 1, PFK);
        const unsigned t_issue = __shfl_sync(0xffffffffu, t_start, 0) + (unsigned)(int)(PT0 + (kb - PW0) * (1000.f / PRATE));
#pragma unroll 1
        for (int q = 4; q < NPIECE; q++) {
            if (lane == q) {
                mbar_wait(fb - min(DMAX, q) * 8);
                unsigned it = 0;
                while (!mbar_test(fb - DMIN * 8) && ++it < SPIN_LIMIT) {
                    unsigned now;
                    asm volatile("mov.u32 %0, %%globaltimer_lo;" : "=r"(now));
                    if ((int)(now - t_issue) >= 0) break;
                }
                if (q >= NSLOT) mbar_wait(sb + SM_EMPTY + (q - NSLOT) * 8);
                mbar_expect_tx(fb, bytes);
                tma_3d(sb + slot_of(p) * SLOT, &maps.m[mi], c0, c1, 0, fb);
            }
            __syncwarp();
        }
        TS(2);
        return;
    }

    const int g8 = lane >> 2, t4 = lane & 3;
    uint32_t* const gx = g_x;

    if (warp < 4) {
        const uint32_t* xw = reinterpret_cast<const uint32_t*>(x + warp * D_);
        uint32_t w[9];
#pragma unroll
        for (int j = 0; j < 9; j++) w[j] = __ldg(xw + lane + 32 * j);
        uint32_t us[3];
#pragma unroll
        for (int j = 0; j < 3; j++) us[j] = __ldg(xw + cg * 72 + min(lane + 32 * j, 71));
        float s = 0.f;
#pragma unroll
        for (int j = 0; j < 9; j++) s += __uint_as_float(w[j] << 16) + __uint_as_float(w[j] & 0xffff0000u);
#pragma unroll
        for (int o = 16; o > 0; o >>= 1) s += __shfl_xor_sync(0xffffffffu, s, o);
        const float mean = s * (1.0f / D_);
        float q = 0.f;
#pragma unroll
        for (int j = 0; j < 9; j++) {
            const float d0 = __uint_as_float(w[j] << 16) - mean, d1 = __uint_as_float(w[j] & 0xffff0000u) - mean;
            q += d0 * d0 + d1 * d1;
        }
#pragma unroll
        for (int o = 16; o > 0; o >>= 1) q += __shfl_xor_sync(0xffffffffu, q, o);
        const float mb = bf16r(mean);
        const float rden = __frcp_rn(bf16r(__fsqrt_rn(bf16r(bf16r(q * (1.0f / D_)) + 1e-5f))));
#pragma unroll
        for (int j = 0; j < 3; j++) {
            const int e2 = min(lane + 32 * j, 71);
            const float v0 = __uint_as_float(us[j] << 16), v1 = __uint_as_float(us[j] & 0xffff0000u);
            sts32(sb + SM_XN + bv_off(e2, warp), pack_bf16(bf16r(v0 - mb) * rden, bf16r(v1 - mb) * rden));
            sts64f(sb + SM_X + (warp * 144 + 2 * e2) * 4, v0, v1);
        }
    } else if (warp == 4) {
        if (lane == 0) {
            unsigned e;
            asm volatile("ld.relaxed.gpu.global.u32 %0, [%1];" : "=r"(e) : "l"(gx + G_EPOCH) : "memory");
            sts32(sb + SM_TAG, e);
        }
    }
    bar_sync(BAR_INIT, NTHREADS);
    const unsigned epoch = __float_as_uint(ldsf(sb + SM_TAG));
    const uint32_t tag = epoch % 15u + 1u;

    if (warp >= 13) {
        const int gw = warp - 13;
        const int task = ci + 32 * gw;
        const int tb = task < 72 ? task / 18 : 0, tc = task < 72 ? (task % 18) * 8 : 0;
#pragma unroll 1
        for (int pass = DRYB; pass < 2; pass++) {
            int real = pass;
            asm volatile("" : "+r"(real));
            if (real) {
                {
                    const int e2 = gw * 32 + lane;
                    if (e2 < 72) {
                        const uint32_t u = __ldg(reinterpret_cast<const uint32_t*>(b1 + ci * 144) + e2);
                        sts64f(sb + SM_B1 + e2 * 8, __uint_as_float(u << 16), __uint_as_float(u & 0xffff0000u));
                    }
                }
                mbar_wait(sb + SM_FULL + (P_K + 7) * 8);
                const int rg = lane >> 3, j = lane & 7;
                const uint32_t* base = gx + G_HP + ((ci * 4 + rg) * B_ + gw) * 144 + j * 4;
                const uint32_t* const p[5] = {base, base + 32, base + 64, base + 96, base + (j < 4 ? 128 : 96)};
                uint4 v[5];
                gather_n<5>(p, v, tag, false, 300);
#pragma unroll
                for (int n = 0; n < 5; n++) {
                    const bool u16 = lane & 16, u8 = lane & 8;
                    const float k0 = untag(u16 ? v[n].z : v[n].x), k1 = untag(u16 ? v[n].w : v[n].y);
                    const float s0 = untag(u16 ? v[n].x : v[n].z), s1 = untag(u16 ? v[n].y : v[n].w);
                    const float a = k0 + __shfl_xor_sync(0xffffffffu, s0, 16);
                    const float b = k1 + __shfl_xor_sync(0xffffffffu, s1, 16);
                    const float h = (u8 ? b : a) + __shfl_xor_sync(0xffffffffu, u8 ? a : b, 8);
                    stsf(sb + SM_HS + (gw * 144 + ((n == 4 && j >= 4) ? 96 : n * 32) + j * 4 + rg) * 4, h);
                }
                bar_sync(BAR_G, 128);
#pragma unroll 1
                for (int f = lane; f < 144; f += 32)
                    sts16(sb + SM_ACT + bv_off(f >> 1, gw) + (f & 1) * 2,
                          __float2bfloat16_rn(mish(ldsf(sb + SM_HS + (gw * 144 + f) * 4) + ldsf(sb + SM_B1 + f * 4))));
                bar_arrive(BAR_ACT, 128 + 288);
                if (gw == 0) TS(6);
                if (task >= 72) return;
                mbar_wait(sb + SM_FULL + (P_WO + 2) * 8);
            }
            const uint32_t* fbase = gx + G_FP + ((cg * 32 + (lane >> 1)) * B_ + tb) * 144 + tc + (lane & 1) * 4;
            const int ocol = tc + (lane & 1) * 4 + ((lane >> 4) & 1) * 2 + ((lane >> 3) & 1);
            const float xv = ldsf(sb + SM_X + (tb * 144 + ocol) * 4);
            uint4 v0 = make_uint4(0, 0, 0, 0), v1 = v0;
            unsigned it = real ? 0u : SPIN_LIMIT;
#pragma unroll 1
            while (true) {
                if (real && !tag_ok(v0, tag)) v0 = ld_poll(fbase);
                if (real && !tag_ok(v1, tag)) v1 = ld_poll(fbase + 16 * B_ * 144);
                if ((tag_ok(v0, tag) && tag_ok(v1, tag)) || ++it > SPIN_LIMIT) break;
                if (!mbar_test(sb + SM_DONE)) __nanosleep(FSLEEP);
            }
            __syncwarp();
            const float r0 = untag(v0.x) + untag(v1.x), r1 = untag(v0.y) + untag(v1.y);
            const float r2 = untag(v0.z) + untag(v1.z), r3 = untag(v0.w) + untag(v1.w);
            const bool u16 = lane & 16, u8 = lane & 8;
            const float sa = (u16 ? r2 : r0) + __shfl_xor_sync(0xffffffffu, u16 ? r0 : r2, 16);
            const float sc = (u16 ? r3 : r1) + __shfl_xor_sync(0xffffffffu, u16 ? r1 : r3, 16);
            float s1 = (u8 ? sc : sa) + __shfl_xor_sync(0xffffffffu, u8 ? sa : sc, 8);
            s1 += __shfl_xor_sync(0xffffffffu, s1, 4);
            s1 += __shfl_xor_sync(0xffffffffu, s1, 2);
            if (real && (lane & 6) == 0) out[tb * D_ + cg * 144 + ocol] = __float2bfloat16_rn(xv + s1);
            if (real && cta == 0 && gw == 0 && lane == 0) {
                st_pub(gx + G_EPOCH, epoch + 1u);
            }
            if (real && gw == 0) TS(14);
        }
        return;
    }

    if (warp >= 9) {
        const int gw = warp - 9;
        {
            mbar_wait(sb + SM_FULL + (P_W1 + 2) * 8);
            const int hh = gw >> 1, rg = lane >> 3, q0 = (gw & 1) * 64 + (lane & 7) * 4;
            const uint32_t* qbase = gx + G_QP + (((2 * hkv + hh) * 4 + rg) * B_ + ab) * DH_ + q0;
            const uint32_t* const pq[2] = {qbase, qbase + 32};
            uint4 vq[2];
            gather_n<2>(pq, vq, tag, false, 200);
#pragma unroll
            for (int n = 0; n < 2; n++) {
                float a = untag(vq[n].x), b = untag(vq[n].y), c = untag(vq[n].z), d = untag(vq[n].w);
#pragma unroll
                for (int o = 8; o <= 16; o <<= 1) {
                    a += __shfl_xor_sync(0xffffffffu, a, o);
                    b += __shfl_xor_sync(0xffffffffu, b, o);
                    c += __shfl_xor_sync(0xffffffffu, c, o);
                    d += __shfl_xor_sync(0xffffffffu, d, o);
                }
                if (rg == 0) {
                    const uint32_t a_ = sb + SM_Q + bv_off((q0 + n * 32) >> 1, hh);
                    sts32(a_, pack_bf16(a, b));
                    sts32(a_ + 8, pack_bf16(c, d));
                }
            }
            bar_arrive(BAR_Q, 128 + 256);
            if (gw == 0) TS(7);
        }
        if (gw == 0) {
            mbar_wait(sb + SM_FULL + (P_V + 2) * 8);
            const uint32_t* const ps[1] = {gx + G_ST + ((hkv * B_ + ab) * 2 + (asplit ^ (lane & 1))) * 8};
            uint4 vs[1];
            gather_n<1>(ps, vs, tag, false, 200);
            const int hh = (lane >> 1) & 1;
            const float ms = untag(hh ? vs[0].z : vs[0].x), ls = untag(hh ? vs[0].w : vs[0].y);
            const float mo = __shfl_xor_sync(0xffffffffu, ms, 1), lo = __shfl_xor_sync(0xffffffffu, ls, 1);
            const float m = fmaxf(ms, mo);
            const float es = exp2f(ms - m), eo = exp2f(mo - m);
            if (lane == 0 || lane == 2) stsf(sb + SM_W + hh * 4, es / (ls * es + lo * eo));
            bar_arrive(BAR_W, 32 + 256);
        }
        {
            mbar_wait(sb + SM_FULL + (OWAIT) * 8);
            const int sp = lane >> 4, d0 = (lane & 15) * 4;
            const uint32_t* base = gx + G_OP + ((ci * B_ + gw) * 2 + sp) * DH_ + d0;
            const uint32_t* const p[2] = {base, base + 64};
            uint4 v[2];
            gather_n<2>(p, v, tag, OREP && (lane & 15) == 0, OSLEEP, gw == 0 ? 21 : -1);
            const uint4 keep = sp ? v[1] : v[0], send = sp ? v[0] : v[1];
            const float a = untag(keep.x) + __shfl_xor_sync(0xffffffffu, untag(send.x), 16);
            const float b = untag(keep.y) + __shfl_xor_sync(0xffffffffu, untag(send.y), 16);
            const float c = untag(keep.z) + __shfl_xor_sync(0xffffffffu, untag(send.z), 16);
            const float d = untag(keep.w) + __shfl_xor_sync(0xffffffffu, untag(send.w), 16);
            const uint32_t a_ = sb + SM_O + bv_off((d0 + sp * 64) >> 1, gw);
            sts32(a_, pack_bf16(a, b));
            sts32(a_ + 8, pack_bf16(c, d));
            bar_arrive(BAR_O, 128 + 288);
            if (gw == 0) TS(12);
        }
        return;
    }

    if (warp == 0) TS(3);
    const int lrow = (lane & 7) + ((lane >> 4) << 3);
    const int lchk = (lane >> 3) & 1;
    const uint32_t off_sw = lrow * 128 + ((((warp & 3) * 2 + lchk) ^ (lane & 7)) << 4);
    const uint32_t off_ln = lrow * 288 + (warp * 2 + lchk) * 16;
    const uint32_t bv_lane = (g8 & 3) * 32 + t4 * 8;
    uint32_t* const pub_f = gx + G_FP + ((cg * 32 + ci) * B_ + 2 * t4) * 144 + warp * 16 + g8;
    uint32_t* const pub_h = gx + G_HP + ((ci * 4 + cg) * B_ + 2 * t4) * 144 + warp * 16 + g8;
    uint32_t* const pub_o = gx + G_OP + ((2 * hkv * B_ + ab) * 2 + asplit) * DH_ + warp * 16 + g8;

    if (t4 == 0 && warp < 8) st_pub4(pub_o, B_ * 2 * DH_, 0u, 0u, 0u, 0u);

    if (DRYC && t4 < 2) st_pub4(pub_f, 144, 0u, 0u, 0u, 0u);
#pragma unroll 1
    for (int pass = DRYC; pass < 2; pass++) {
    int real = pass;
    asm volatile("" : "+r"(real));
    if (real) {
#pragma unroll 1
    for (int phi = 0; phi < 3; phi++) {
        const int ph = phi == 0 ? 0 : 3 - phi;
        const bool wide = ph == 2;
        if (ph == 1 && warp < 8) {
            bar_sync(BAR_Q, 128 + 256);
            uint2 qa[8];
#pragma unroll
            for (int kk = 0; kk < 8; kk++) qa[kk] = lds64(sb + SM_Q + kk * 128 + (g8 & 1) * 32 + t4 * 8);
            const int key = warp * 8 + (lane & 7);
            const uint32_t koff = key * 128;
            const uint32_t kx0 = ((lane >> 3) ^ (key & 7)) << 4, kx1 = (((lane >> 3) + 4) ^ (key & 7)) << 4;
            float mx = -INFINITY;
#pragma unroll 1
            for (int j = 0; j < 8; j++) {
                mbar_wait(sb + SM_FULL + (P_K + j) * 8);
                const uint32_t ka = sb + slot_of(P_K + j) * SLOT + koff;
                float c0[4] = {0.f, 0.f, 0.f, 0.f}, c1[4] = {0.f, 0.f, 0.f, 0.f};
#pragma unroll
                for (int qd = 0; qd < 4; qd++) {
                    uint32_t r0, r1, r2, r3;
                    ldsm_x4(ka + (qd >> 1) * 8192 + ((qd & 1) ? kx1 : kx0), r0, r1, r2, r3);
                    mma16816(c0, qa[2 * qd].x, qa[2 * qd].x, qa[2 * qd].y, qa[2 * qd].y, r0, r1);
                    mma16816(c1, qa[2 * qd + 1].x, qa[2 * qd + 1].x, qa[2 * qd + 1].y, qa[2 * qd + 1].y, r2, r3);
                }
                __syncwarp();
                if (lane == 0) mbar_arrive(sb + SM_EMPTY + (P_K + j) * 8);
                const float s0 = c0[0] + c1[0], s1 = c0[1] + c1[1];
                mx = fmaxf(mx, fmaxf(s0, s1));
                if (g8 < 2) sts64f(sb + SM_SC + (((4 * j + (warp >> 1)) * 2 + g8) * 8 + t4 * 2 + (warp & 1)) * 8, s0, s1);
            }
            if (warp == 0) TS(8);
            mx = fmaxf(mx, __shfl_xor_sync(0xffffffffu, mx, 1));
            mx = fmaxf(mx, __shfl_xor_sync(0xffffffffu, mx, 2));
            if (g8 < 2 && t4 == 0) stsf(sb + SM_RED + (warp * 2 + g8) * 4, mx);
            bar_sync(BAR_CMP, 256);
            const float kScale = 0.08838834764831845f * 1.4426950408889634f;
            const int hh = (tid >> 3) & 1;
            float m = ldsf(sb + SM_RED + ((lane & 7) * 2 + hh) * 4);
            m = fmaxf(m, __shfl_xor_sync(0xffffffffu, m, 1));
            m = fmaxf(m, __shfl_xor_sync(0xffffffffu, m, 2));
            m = fmaxf(m, __shfl_xor_sync(0xffffffffu, m, 4));
            m *= kScale;
            float l = 0.f;
#pragma unroll
            for (int n = 0; n < 2; n++) {
                const int idx = tid + n * 256;
                const uint2 s = lds64(sb + SM_SC + idx * 8);
                const float p0 = exp2f(fmaf(__uint_as_float(s.x), kScale, -m));
                const float p1 = exp2f(fmaf(__uint_as_float(s.y), kScale, -m));
                l += p0 + p1;
                sts32(sb + SM_P + ((idx >> 4) * 32 + (idx & 15)) * 4, pack_bf16(p0, p1));
            }
            l += __shfl_xor_sync(0xffffffffu, l, 1);
            l += __shfl_xor_sync(0xffffffffu, l, 2);
            l += __shfl_xor_sync(0xffffffffu, l, 4);
            l += __shfl_xor_sync(0xffffffffu, l, 16);
            if (lane < 16 && (lane & 7) == 0) stsf(sb + SM_RED + (16 + warp * 2 + hh) * 4, l);
            bar_sync(BAR_CMP, 256);
            if (warp == 0) {
                float ls = ldsf(sb + SM_RED + (16 + (lane & 7) * 2 + hh) * 4);
                ls += __shfl_xor_sync(0xffffffffu, ls, 1);
                ls += __shfl_xor_sync(0xffffffffu, ls, 2);
                ls += __shfl_xor_sync(0xffffffffu, ls, 4);
                if ((lane & 6) == 0)
                    st_pub(gx + G_ST + ((hkv * B_ + ab) * 2 + asplit) * 8 + (lane >> 4) * 4 + hh * 2 + (lane & 1),
                           tagw((lane & 1) ? ls : m, tag));
                TS(9);
            }
        }
        if (wide || warp < 8) {
            const int p0 = ph == 0 ? P_WQ : ph == 1 ? P_V : P_W1;
            const int np = ph == 1 ? 8 : 3;
            const int kpp = ph == 1 ? 4 : 3;
            const uint32_t aoff = wide ? off_ln : off_sw + (warp >> 2) * (ph == 0 ? 6144 : 8192);
            const uint32_t kstr = wide ? 16 * 288 : 16 * 128;
            uint32_t bv = sb + bv_lane + (ph == 1 ? SM_P : SM_XN);
            float acc[4] = {0.f, 0.f, 0.f, 0.f}, acd[4] = {0.f, 0.f, 0.f, 0.f};
#pragma unroll 1
            for (int p = p0; p < p0 + np; p++) {
                uint2 b[4];
#pragma unroll
                for (int ks = 0; ks < 4; ks++) b[ks] = lds64(bv + ks * 128);
                mbar_wait(sb + SM_FULL + p * 8);
                const uint32_t aa = sb + slot_of(p) * SLOT + aoff;
                uint32_t a[4][4];
#pragma unroll
                for (int ks = 0; ks < 4; ks++)
                    if (ks < 3 || kpp == 4) ldsm_x4_t(aa + ks * kstr, a[ks][0], a[ks][1], a[ks][2], a[ks][3]);
                mma16816(acc, a[0][0], a[0][1], a[0][2], a[0][3], b[0].x, b[0].y);
                mma16816(acd, a[1][0], a[1][1], a[1][2], a[1][3], b[1].x, b[1].y);
                mma16816(acc, a[2][0], a[2][1], a[2][2], a[2][3], b[2].x, b[2].y);
                if (kpp == 4) mma16816(acd, a[3][0], a[3][1], a[3][2], a[3][3], b[3].x, b[3].y);
                bv += kpp * 128;
                __syncwarp();
                if (lane == 0 && p < NEMPTY) mbar_arrive(sb + SM_EMPTY + p * 8);
                if (ph == 1 && p == p0 + np - 2) bar_sync(BAR_W, 32 + 256);
            }
            float w0 = 1.f, w1 = 1.f;
            if (ph == 1) { w0 = ldsf(sb + SM_W); w1 = ldsf(sb + SM_W + 4); }
            uint32_t* d0 = ph == 0 ? gx + G_QP + ((ci * 4 + cg) * B_ + 2 * t4) * DH_ + warp * 16 + g8
                         : ph == 1 ? pub_o : pub_h;
            if (t4 < (ph == 1 ? 1 : 2))
                st_pub4(d0, ph == 0 ? DH_ : ph == 1 ? B_ * 2 * DH_ : 144, tagw((acc[0] + acd[0]) * w0, tag),
                        tagw((acc[1] + acd[1]) * w1, tag), tagw((acc[2] + acd[2]) * w0, tag),
                        tagw((acc[3] + acd[3]) * w1, tag));
        }
        if (warp == 0) TS(ph == 0 ? 4 : ph == 1 ? 10 : 5);
    }

    }

    {
        float c0[4] = {0.f, 0.f, 0.f, 0.f}, c1[4] = {0.f, 0.f, 0.f, 0.f};
        if (real) bar_sync(BAR_ACT, 128 + 288);
#pragma unroll
        for (int p = 0; p < 3; p++) {
            if (real) mbar_wait(sb + SM_FULL + (P_W2 + p) * 8);
#pragma unroll
            for (int ks = 0; ks < 3; ks++) {
                uint32_t a0, a1, a2, a3;
                ldsm_x4_t(sb + slot_of(P_W2 + p) * SLOT + off_ln + ks * 16 * 288, a0, a1, a2, a3);
                const uint2 b = lds64(sb + bv_lane + SM_ACT + (p * 3 + ks) * 128);
                if (ks & 1) mma16816(c1, a0, a1, a2, a3, b.x, b.y);
                else mma16816(c0, a0, a1, a2, a3, b.x, b.y);
            }
        }
        if (real && warp == 0) TS(11);
        uint32_t a[6][4];
#pragma unroll
        for (int p = 0; p < 3; p++) {
            if (real) mbar_wait(sb + SM_FULL + (P_WO + p) * 8);
#pragma unroll
            for (int ks = 0; ks < 2; ks++)
                ldsm_x4_t(sb + slot_of(P_WO + p) * SLOT + off_ln + ks * 16 * 288,
                          a[2 * p + ks][0], a[2 * p + ks][1], a[2 * p + ks][2], a[2 * p + ks][3]);
        }
        if (real && warp == 0) TS(17);
        if (real) bar_sync(BAR_O, 128 + 288);
        uint2 b[8];
#pragma unroll
        for (int k = 0; k < 8; k++) b[k] = lds64(sb + bv_lane + SM_O + k * 128);
#pragma unroll
        for (int k = 0; k < 6; k++) {
            if (k & 1) mma16816(c1, a[k][0], a[k][1], a[k][2], a[k][3], b[k].x, b[k].y);
            else mma16816(c0, a[k][0], a[k][1], a[k][2], a[k][3], b[k].x, b[k].y);
        }
        if (real && warp == 0) TS(16);
        if (real) mbar_wait(sb + SM_FULL + (P_WO + 3) * 8);
        if (real && warp == 0) TS(20);
        ldsm_x4_t(sb + slot_of(P_WO + 3) * SLOT + off_ln, a[0][0], a[0][1], a[0][2], a[0][3]);
        ldsm_x4_t(sb + slot_of(P_WO + 3) * SLOT + off_ln + 16 * 288, a[1][0], a[1][1], a[1][2], a[1][3]);
        mma16816(c0, a[0][0], a[0][1], a[0][2], a[0][3], b[6].x, b[6].y);
        mma16816(c1, a[1][0], a[1][1], a[1][2], a[1][3], b[7].x, b[7].y);
        const uint32_t msk = real ? 0xffffffffu : 0u;
        if (t4 < 2)
            st_pub4(pub_f, 144, tagw(c0[0] + c1[0], tag) & msk, tagw(c0[1] + c1[1], tag) & msk,
                    tagw(c0[2] + c1[2], tag) & msk, tagw(c0[3] + c1[3], tag) & msk);
        __syncwarp();
        if (real && lane == 0) mbar_arrive(sb + SM_DONE);
        if (real && warp == 0) TS(13);
    }
    }
}

typedef CUresult (*EncodeTiledFn)(CUtensorMap*, CUtensorMapDataType, cuuint32_t, void*, const cuuint64_t*,
                                  const cuuint64_t*, const cuuint32_t*, const cuuint32_t*, CUtensorMapInterleave,
                                  CUtensorMapSwizzle, CUtensorMapL2promotion, CUtensorMapFloatOOBfill);

void make_map_lin(EncodeTiledFn fn, CUtensorMap* tm, const void* ptr, uint64_t cols, uint64_t rows, uint32_t box_rows) {
    cuuint64_t gdim[3] = {cols, rows, 1};
    cuuint64_t gstr[2] = {cols * 2, cols * rows * 2};
    cuuint32_t box[3] = {144, box_rows, 1};
    cuuint32_t estr[3] = {1, 1, 1};
    fn(tm, CU_TENSOR_MAP_DATA_TYPE_BFLOAT16, 3, const_cast<void*>(ptr), gdim, gstr, box, estr,
       CU_TENSOR_MAP_INTERLEAVE_NONE, CU_TENSOR_MAP_SWIZZLE_NONE, CU_TENSOR_MAP_L2_PROMOTION_L2_256B,
       CU_TENSOR_MAP_FLOAT_OOB_FILL_NONE);
}
void make_map_sw(EncodeTiledFn fn, CUtensorMap* tm, const void* ptr, uint64_t cols, uint64_t rows, uint32_t box_rows) {
    cuuint64_t gdim[3] = {64, rows, cols / 64};
    cuuint64_t gstr[2] = {cols * 2, 128};
    cuuint32_t box[3] = {64, box_rows, 2};
    cuuint32_t estr[3] = {1, 1, 1};
    fn(tm, CU_TENSOR_MAP_DATA_TYPE_BFLOAT16, 3, const_cast<void*>(ptr), gdim, gstr, box, estr,
       CU_TENSOR_MAP_INTERLEAVE_NONE, CU_TENSOR_MAP_SWIZZLE_128B, CU_TENSOR_MAP_L2_PROMOTION_L2_256B,
       CU_TENSOR_MAP_FLOAT_OOB_FILL_NONE);
}

}

extern "C" void kernel_launch(void* const* d_in, const int* in_sizes, int n_in, void* d_out, int out_size) {
    (void)in_sizes; (void)n_in; (void)out_size;
    static EncodeTiledFn encode = nullptr;
    if (!encode) {
        void* fn = nullptr;
        cudaDriverEntryPointQueryResult st;
        cudaGetDriverEntryPoint("cuTensorMapEncodeTiled", &fn, cudaEnableDefault, &st);
        encode = (EncodeTiledFn)fn;
        cudaFuncSetAttribute(fused_decode_kernel, cudaFuncAttributeMaxDynamicSharedMemorySize, SMEM_BYTES);
    }
    Maps maps;
    make_map_sw(encode, &maps.m[0], d_in[3], HQ_ * DH_, D_, 48);
    make_map_sw(encode, &maps.m[1], d_in[1], DH_, (uint64_t)B_ * HKV_ * SK_, 64);
    make_map_sw(encode, &maps.m[2], d_in[2], DH_, (uint64_t)B_ * HKV_ * SK_, 64);
    make_map_lin(encode, &maps.m[3], d_in[6], F_, D_, 48);
    make_map_lin(encode, &maps.m[4], d_in[8], D_, F_, 48);
    make_map_lin(encode, &maps.m[5], d_in[4], D_, HQ_ * DH_, 32);
    fused_decode_kernel<<<NCTA, NTHREADS, SMEM_BYTES>>>(maps, (const __nv_bfloat16*)d_in[0],
                                                        (const __nv_bfloat16*)d_in[7], (__nv_bfloat16*)d_out,
                                                        (const __nv_bfloat16*)d_in[1]);
}
```

```cpp
#include <cuda_runtime.h>
#include <cuda_bf16.h>
#include <cuda.h>
#include <stdint.h>

namespace {

constexpr int D_ = 576, HQ_ = 32, HKV_ = 16, SK_ = 4096, DH_ = 128, W_ = 1024, F_ = 4608, B_ = 4;
constexpr int NCTA = 128;
constexpr int PROD_WARP = 17;
constexpr int NTHREADS = 576;
#define DMIN 2
#define DMAX 6
#define PRATE 25.25f
#define PW0 26.f
#define PT0 500.f
#define OWAIT (P_W2)
#define PW1 36.f
#define QSW 25
#define NFIRST 3
#define QWAIT (P_K + 2)
#define OSLEEP 200
#define FSLEEP 200
constexpr int SLOT = 16384;
constexpr int NSLOT = 13;
constexpr int P_WQ = 0, P_W1 = 3, P_K = 6, P_V = 14, P_W2 = 22, P_WO = 25, NPIECE = 29;
constexpr int NEMPTY = NPIECE - NSLOT;

constexpr int SM_RING = 0;
constexpr int SM_XN = NSLOT * SLOT;
constexpr int SM_ACT = SM_XN + 9 * 128;
constexpr int SM_O = SM_ACT + 9 * 128;
constexpr int SM_Q = SM_O + 8 * 128;
constexpr int SM_P = SM_Q + 8 * 128;
constexpr int SM_SC = SM_P + 32 * 128;
constexpr int SM_X = SM_SC + 512 * 8;
constexpr int SM_B1 = SM_X + 4 * 144 * 4;
constexpr int SM_HS = SM_B1 + 144 * 4;
constexpr int SM_RED = SM_HS + 4 * 144 * 4;
constexpr int SM_W = SM_RED + 32 * 4;
constexpr int SM_FULL = SM_W + 8;
constexpr int SM_EMPTY = SM_FULL + NPIECE * 8;
constexpr int SM_DONE = SM_EMPTY + NEMPTY * 8;
constexpr int SM_TAG = SM_DONE + 8;
constexpr int SM_TOTAL = SM_TAG + 16;
constexpr int SMEM_BYTES = SM_TOTAL + 1024;

constexpr unsigned SPIN_LIMIT = 1u << 21;

constexpr int BAR_CMP = 1;
constexpr int BAR_Q = 2;
constexpr int BAR_ACT = 3;
constexpr int BAR_O = 4;
constexpr int BAR_INIT = 5;
constexpr int BAR_G = 6;
constexpr int BAR_W = 7;

constexpr int G_QP = 0;
constexpr int G_HP = G_QP + HQ_ * 4 * B_ * DH_;
constexpr int G_OP = G_HP + 32 * 4 * B_ * 144;
constexpr int G_ST = G_OP + HQ_ * B_ * 2 * DH_;
constexpr int G_FP = G_ST + HKV_ * B_ * 2 * 8;
constexpr int G_EPOCH = G_FP + 4 * 32 * B_ * 144;
__device__ __align__(256) uint32_t g_x[G_EPOCH + 64];

#define TS(idx) do {} while (0)
#define TSA(idx) do {} while (0)
#define TSG(idx) do {} while (0)

__device__ __forceinline__ uint32_t smem_u32(const void* p) { return (uint32_t)__cvta_generic_to_shared(p); }
__device__ __forceinline__ void mbar_init(uint32_t bar, uint32_t cnt) {
    asm volatile("mbarrier.init.shared::cta.b64 [%0], %1;" ::"r"(bar), "r"(cnt) : "memory");
}
__device__ __forceinline__ void mbar_expect_tx(uint32_t bar, uint32_t bytes) {
    asm volatile("mbarrier.arrive.expect_tx.shared::cta.b64 _, [%0], %1;" ::"r"(bar), "r"(bytes) : "memory");
}
__device__ __forceinline__ void mbar_arrive(uint32_t bar) {
    asm volatile("mbarrier.arrive.shared::cta.b64 _, [%0];" ::"r"(bar) : "memory");
}
__device__ __forceinline__ bool mbar_test(uint32_t bar) {
    uint32_t ok;
    asm volatile(
        "{\n.reg .pred p;\n"
        "mbarrier.test_wait.parity.shared::cta.b64 p, [%1], 0;\n"
        "selp.u32 %0, 1, 0, p;\n}"
        : "=r"(ok) : "r"(bar) : "memory");
    return ok != 0;
}
__device__ __forceinline__ void mbar_wait(uint32_t bar) {
    asm volatile(
        "{\n.reg .pred p;\n.reg .u32 c;\n"
        "mov.u32 c, 0;\n"
        "W_%=:\n"
        "mbarrier.try_wait.parity.shared::cta.b64 p, [%0], 0;\n"
        "@p bra D_%=;\n"
        "add.u32 c, c, 1;\n"
        "setp.lt.u32 p, c, %1;\n"
        "@p bra W_%=;\n"
        "D_%=:\n}"
        ::"r"(bar), "n"(SPIN_LIMIT) : "memory");
}
__device__ __forceinline__ void tma_3d(uint32_t dst, const CUtensorMap* tm, int c0, int c1, int c2, uint32_t bar) {
    uint64_t pol;
    asm volatile("createpolicy.fractional.L2::evict_first.b64 %0, 1.0;" : "=l"(pol));
    asm volatile(
        "cp.async.bulk.tensor.3d.shared::cluster.global.mbarrier::complete_tx::bytes.L2::cache_hint"
        " [%0], [%1, {%3, %4, %5}], [%2], %6;"
        ::"r"(dst), "l"(tm), "r"(bar), "r"(c0), "r"(c1), "r"(c2), "l"(pol) : "memory");
}
__device__ __forceinline__ void prefetch_tm(const CUtensorMap* tm) {
    asm volatile("prefetch.tensormap [%0];" ::"l"(tm) : "memory");
}
__device__ __forceinline__ void ldsm_x4(uint32_t addr, uint32_t& r0, uint32_t& r1, uint32_t& r2, uint32_t& r3) {
    asm volatile("ldmatrix.sync.aligned.m8n8.x4.shared.b16 {%0,%1,%2,%3}, [%4];"
                 : "=r"(r0), "=r"(r1), "=r"(r2), "=r"(r3) : "r"(addr) : "memory");
}
__device__ __forceinline__ void ldsm_x4_t(uint32_t addr, uint32_t& r0, uint32_t& r1, uint32_t& r2, uint32_t& r3) {
    asm volatile("ldmatrix.sync.aligned.m8n8.x4.trans.shared.b16 {%0,%1,%2,%3}, [%4];"
                 : "=r"(r0), "=r"(r1), "=r"(r2), "=r"(r3) : "r"(addr) : "memory");
}
__device__ __forceinline__ void mma16816(float (&c)[4], uint32_t a0, uint32_t a1, uint32_t a2, uint32_t a3,
                                         uint32_t b0, uint32_t b1) {
    asm volatile(
        "mma.sync.aligned.m16n8k16.row.col.f32.bf16.bf16.f32 {%0,%1,%2,%3}, {%4,%5,%6,%7}, {%8,%9}, {%0,%1,%2,%3};"
        : "+f"(c[0]), "+f"(c[1]), "+f"(c[2]), "+f"(c[3])
        : "r"(a0), "r"(a1), "r"(a2), "r"(a3), "r"(b0), "r"(b1));
}
__device__ __forceinline__ void bar_sync(int id, int nthreads) {
    asm volatile("bar.sync %0, %1;" ::"r"(id), "r"(nthreads) : "memory");
}
__device__ __forceinline__ void bar_arrive(int id, int nthreads) {
    asm volatile("bar.arrive %0, %1;" ::"r"(id), "r"(nthreads) : "memory");
}
__device__ __forceinline__ uint2 lds64(uint32_t a) {
    uint2 v; asm volatile("ld.shared.v2.u32 {%0,%1}, [%2];" : "=r"(v.x), "=r"(v.y) : "r"(a) : "memory"); return v;
}
__device__ __forceinline__ float ldsf(uint32_t a) {
    float v; asm volatile("ld.shared.f32 %0, [%1];" : "=f"(v) : "r"(a) : "memory"); return v;
}
__device__ __forceinline__ void sts32(uint32_t a, uint32_t v) {
    asm volatile("st.shared.u32 [%0], %1;" ::"r"(a), "r"(v) : "memory");
}
__device__ __forceinline__ void stsf(uint32_t a, float v) {
    asm volatile("st.shared.f32 [%0], %1;" ::"r"(a), "f"(v) : "memory");
}
__device__ __forceinline__ void sts64f(uint32_t a, float v0, float v1) {
    asm volatile("st.shared.v2.f32 [%0], {%1,%2};" ::"r"(a), "f"(v0), "f"(v1) : "memory");
}
__device__ __forceinline__ void sts16(uint32_t a, __nv_bfloat16 v) {
    asm volatile("st.shared.u16 [%0], %1;" ::"r"(a), "h"(__bfloat16_as_ushort(v)) : "memory");
}
__device__ __forceinline__ uint32_t tagw(float v, uint32_t tag) { return (__float_as_uint(v) & ~15u) | tag; }
__device__ __forceinline__ void st_pub(uint32_t* p, uint32_t v) {
    asm volatile("st.relaxed.gpu.global.u32 [%0], %1;" ::"l"(p), "r"(v) : "memory");
}
__device__ __forceinline__ void st_pub4(uint32_t* d0, int S, uint32_t w0, uint32_t w1, uint32_t w2, uint32_t w3) {
    st_pub(d0, w0); st_pub(d0 + S, w1); st_pub(d0 + 8, w2); st_pub(d0 + S + 8, w3);
}
__device__ __forceinline__ uint4 ld_poll(const uint32_t* p) {
    uint4 v;
    asm volatile("ld.relaxed.gpu.global.v4.u32 {%0,%1,%2,%3}, [%4];"
                 : "=r"(v.x), "=r"(v.y), "=r"(v.z), "=r"(v.w) : "l"(p) : "memory");
    return v;
}
__device__ __forceinline__ bool tag_ok(const uint4& v, uint32_t tag) {
    return ((((v.x ^ tag) | (v.y ^ tag)) | ((v.z ^ tag) | (v.w ^ tag))) & 15u) == 0;
}
template <int N>
__device__ __forceinline__ void gather_n(const uint32_t* const (&p)[N], uint4 (&v)[N], uint32_t tag, unsigned sleep_ns) {
#pragma unroll
    for (int n = 0; n < N; n++) v[n] = make_uint4(0, 0, 0, 0);
    unsigned it = 0;
#pragma unroll 1
    while (true) {
#pragma unroll
        for (int n = 0; n < N; n++)
            if (!tag_ok(v[n], tag)) v[n] = ld_poll(p[n]);
        bool ok = true;
#pragma unroll
        for (int n = 0; n < N; n++) ok = ok && tag_ok(v[n], tag);
        if (ok || ++it > SPIN_LIMIT) break;
        __nanosleep(sleep_ns);
    }
    __syncwarp();
}
__device__ __forceinline__ float untag(uint32_t w) { return __uint_as_float(w & ~15u); }
__device__ __forceinline__ float bf16r(float v) { return __bfloat162float(__float2bfloat16_rn(v)); }
__device__ __forceinline__ uint32_t pack_bf16(float lo, float hi) {
    __nv_bfloat162 h = __floats2bfloat162_rn(lo, hi);
    return *reinterpret_cast<uint32_t*>(&h);
}
__device__ __forceinline__ uint32_t bv_off(int e2, int n) {
    return ((e2 >> 3) * 32 + n * 8 + (e2 & 3) * 2 + ((e2 >> 2) & 1)) * 4;
}
__device__ __forceinline__ float mish(float h) {
    const float e = __expf(fminf(h, 30.f));
    const float n = e * (e + 2.f);
    return h * __fdividef(n, n + 2.f);
}
__device__ __forceinline__ int slot_of(int p) { return p < NSLOT ? p : (p < 2 * NSLOT ? p - NSLOT : p - 2 * NSLOT); }

__device__ __forceinline__ void final_reduce(uint32_t sb, uint32_t* gx, __nv_bfloat16* out, int ci, int cg, int gw, int lane,
                                             uint32_t tag, unsigned epoch, bool bump_epoch) {
    const int task = ci + 32 * gw;
    if (task >= 72) return;
    const int tb = task / 18, tc = (task % 18) * 8;
    const uint32_t* fbase = gx + G_FP + ((cg * 32 + (lane >> 1)) * B_ + tb) * 144 + tc + (lane & 1) * 4;
    const int ocol = tc + (lane & 1) * 4 + ((lane >> 4) & 1) * 2 + ((lane >> 3) & 1);
    const float xv = ldsf(sb + SM_X + (tb * 144 + ocol) * 4);
    uint4 v0 = make_uint4(0, 0, 0, 0), v1 = v0;
    mbar_wait(sb + SM_FULL + (P_WO + 2) * 8);
    unsigned it = 0;
#pragma unroll 1
    while (true) {
        if (!tag_ok(v0, tag)) v0 = ld_poll(fbase);
        if (!tag_ok(v1, tag)) v1 = ld_poll(fbase + 16 * B_ * 144);
        if ((tag_ok(v0, tag) && tag_ok(v1, tag)) || ++it > SPIN_LIMIT) break;
        if (!mbar_test(sb + SM_DONE)) __nanosleep(FSLEEP);
    }
    __syncwarp();
    const float r0 = untag(v0.x) + untag(v1.x), r1 = untag(v0.y) + untag(v1.y);
    const float r2 = untag(v0.z) + untag(v1.z), r3 = untag(v0.w) + untag(v1.w);
    const bool u16 = lane & 16, u8 = lane & 8;
    const float sa = (u16 ? r2 : r0) + __shfl_xor_sync(0xffffffffu, u16 ? r0 : r2, 16);
    const float sc = (u16 ? r3 : r1) + __shfl_xor_sync(0xffffffffu, u16 ? r1 : r3, 16);
    float s1 = (u8 ? sc : sa) + __shfl_xor_sync(0xffffffffu, u8 ? sa : sc, 8);
    s1 += __shfl_xor_sync(0xffffffffu, s1, 4);
    s1 += __shfl_xor_sync(0xffffffffu, s1, 2);
    if ((lane & 6) == 0) out[tb * D_ + cg * 144 + ocol] = __float2bfloat16_rn(xv + s1);
    if (bump_epoch && lane == 0) {
        st_pub(gx + G_EPOCH, epoch + 1u);
    }
    if (gw == 0) TS(14);
}

struct Maps { CUtensorMap m[6]; };

__global__ void __launch_bounds__(NTHREADS, 1)
fused_decode_kernel(const __grid_constant__ Maps maps, const __nv_bfloat16* __restrict__ x,
                    const __nv_bfloat16* __restrict__ b1, __nv_bfloat16* __restrict__ out) {
    extern __shared__ unsigned char smem_raw[];
    const uint32_t sb = (smem_u32(smem_raw) + 1023u) & ~1023u;

    const int tid = threadIdx.x, warp = tid >> 5, lane = tid & 31;
    const int cta = blockIdx.x;
    const int ci = cta >> 2, cg = cta & 3;
    const int hkv = ci >> 1;
    const int bs = ((ci & 1) << 2) | cg;
    const int ab = bs >> 1, asplit = bs & 1;
    const int kv_row0 = (ab * HKV_ + hkv) * SK_ + (SK_ - W_) + asplit * 512;

    unsigned t_start = 0;
    if (tid == PROD_WARP * 32) {
        TSA(0);
#pragma unroll
        for (int p = 0; p < NFIRST; p++) mbar_init(sb + SM_FULL + p * 8, 1);
        asm volatile("fence.mbarrier_init.release.cluster;" ::: "memory");
#pragma unroll
        for (int p = 0; p < (NFIRST < 3 ? NFIRST : 3); p++) {
            mbar_expect_tx(sb + SM_FULL + p * 8, 48 * 256);
            tma_3d(sb + p * SLOT, &maps.m[0], 0, cg * 144 + p * 48, 2 * ci, sb + SM_FULL + p * 8);
        }
#pragma unroll
        for (int p = 3; p < NFIRST; p++) {
            mbar_expect_tx(sb + SM_FULL + p * 8, 48 * 288);
            tma_3d(sb + p * SLOT, &maps.m[3], ci * 144, cg * 144 + (p - 3) * 48, 0, sb + SM_FULL + p * 8);
        }
        asm volatile("mov.u32 %0, %%globaltimer_lo;" : "=r"(t_start));
        TSA(1);
    }

    if (warp == PROD_WARP) {
        const int p = lane;
        int mi, c0 = 0, c1, c2 = 0, bytes = 48 * 288;
        float kb;
        if (p < P_W1)      { mi = 0; c1 = cg * 144 + p * 48; c2 = 2 * ci; bytes = 48 * 256; kb = 12.f * p; }
        else if (p < P_K)  { mi = 3; c0 = ci * 144; c1 = cg * 144 + (p - P_W1) * 48; kb = 36.f + 13.5f * (p - P_W1); }
        else if (p < P_V)  { mi = 1; c1 = kv_row0 + (p - P_K) * 64; bytes = 16384; kb = 76.5f + 16.f * (p - P_K); }
        else if (p < P_W2) { mi = 2; c1 = kv_row0 + (p - P_V) * 64; bytes = 16384; kb = 76.5f + 16.f * (p - P_K); }
        else if (p < P_WO) { mi = 4; c0 = cg * 144; c1 = ci * 144 + (p - P_W2) * 48; kb = 332.5f + 13.5f * (p - P_W2); }
        else { mi = 5; c0 = cg * 144; c1 = ci * 128 + (p - P_WO) * 32; bytes = 32 * 288; kb = 373.f + 9.f * (p - P_WO); }
        const uint32_t fb = sb + SM_FULL + p * 8;
        if (p >= 1 && p < 6) prefetch_tm(&maps.m[p]);
        if (lane == 0) {
#pragma unroll
            for (int q = NFIRST; q < NPIECE; q++) mbar_init(sb + SM_FULL + q * 8, 1);
#pragma unroll
            for (int e = 0; e <= NEMPTY; e++) mbar_init(sb + SM_EMPTY + e * 8, (e == NEMPTY || (e >= P_W1 && e < P_W1 + 3)) ? 9 : 8);
            asm volatile("fence.mbarrier_init.release.cluster;" ::: "memory");
        }
        __syncwarp();
        bar_arrive(BAR_INIT, NTHREADS);
        const unsigned t_issue = __shfl_sync(0xffffffffu, t_start, 0) + (unsigned)(int)(PT0 + (kb - (p < QSW ? PW0 : PW1)) * (1000.f / PRATE));
#pragma unroll 1
        for (int q = NFIRST; q < NPIECE; q++) {
            if (lane == q) {
                mbar_wait(fb - min(DMAX, q) * 8);
                unsigned it = 0;
                while (!mbar_test(fb - min(DMIN, q) * 8) && ++it < SPIN_LIMIT) {
                    unsigned now;
                    asm volatile("mov.u32 %0, %%globaltimer_lo;" : "=r"(now));
                    if ((int)(now - t_issue) >= 0) break;
                }
                if (q >= NSLOT) mbar_wait(sb + SM_EMPTY + (q - NSLOT) * 8);
                mbar_expect_tx(fb, bytes);
                tma_3d(sb + slot_of(p) * SLOT, &maps.m[mi], c0, c1, c2, fb);
            }
            __syncwarp();
        }
        TS(2);
        return;
    }

    const int g8 = lane >> 2, t4 = lane & 3;
    uint32_t* const gx = g_x;

    if (warp < 4) {
        const uint32_t* xw = reinterpret_cast<const uint32_t*>(x + warp * D_);
        uint32_t w[9];
#pragma unroll
        for (int j = 0; j < 9; j++) w[j] = __ldg(xw + lane + 32 * j);
        uint32_t us[3];
#pragma unroll
        for (int j = 0; j < 3; j++) us[j] = __ldg(xw + cg * 72 + min(lane + 32 * j, 71));
        float s = 0.f;
#pragma unroll
        for (int j = 0; j < 9; j++) s += __uint_as_float(w[j] << 16) + __uint_as_float(w[j] & 0xffff0000u);
#pragma unroll
        for (int o = 16; o > 0; o >>= 1) s += __shfl_xor_sync(0xffffffffu, s, o);
        const float mean = s * (1.0f / D_);
        float q = 0.f;
#pragma unroll
        for (int j = 0; j < 9; j++) {
            const float d0 = __uint_as_float(w[j] << 16) - mean, d1 = __uint_as_float(w[j] & 0xffff0000u) - mean;
            q += d0 * d0 + d1 * d1;
        }
#pragma unroll
        for (int o = 16; o > 0; o >>= 1) q += __shfl_xor_sync(0xffffffffu, q, o);
        const float mb = bf16r(mean);
        const float rden = __frcp_rn(bf16r(__fsqrt_rn(bf16r(bf16r(q * (1.0f / D_)) + 1e-5f))));
#pragma unroll
        for (int j = 0; j < 3; j++) {
            const int e2 = min(lane + 32 * j, 71);
            const float v0 = __uint_as_float(us[j] << 16), v1 = __uint_as_float(us[j] & 0xffff0000u);
            sts32(sb + SM_XN + bv_off(e2, warp), pack_bf16(bf16r(v0 - mb) * rden, bf16r(v1 - mb) * rden));
            sts64f(sb + SM_X + (warp * 144 + 2 * e2) * 4, v0, v1);
        }
    } else if (warp == 4) {
        if (lane == 0) {
            unsigned e;
            asm volatile("ld.relaxed.gpu.global.u32 %0, [%1];" : "=r"(e) : "l"(gx + G_EPOCH) : "memory");
            sts32(sb + SM_TAG, e);
        }
    }
    bar_sync(BAR_INIT, NTHREADS);
    const unsigned epoch = __float_as_uint(ldsf(sb + SM_TAG));
    const uint32_t tag = epoch % 15u + 1u;

    if (warp >= 13) {
        const int gw = warp - 13;
        {
            const int e2 = gw * 32 + lane;
            if (e2 < 72) {
                const uint32_t u = __ldg(reinterpret_cast<const uint32_t*>(b1 + ci * 144) + e2);
                sts64f(sb + SM_B1 + e2 * 8, __uint_as_float(u << 16), __uint_as_float(u & 0xffff0000u));
            }
        }
        {
            mbar_wait(sb + SM_FULL + (P_K + 7) * 8);
            const int rg = lane >> 3, j = lane & 7;
            const uint32_t* base = gx + G_HP + ((ci * 4 + rg) * B_ + gw) * 144 + j * 4;
            const uint32_t* const p[5] = {base, base + 32, base + 64, base + 96, base + (j < 4 ? 128 : 96)};
            uint4 v[5];
            gather_n<5>(p, v, tag, 300);
#pragma unroll
            for (int n = 0; n < 5; n++) {
                const bool u16 = lane & 16, u8 = lane & 8;
                const float k0 = untag(u16 ? v[n].z : v[n].x), k1 = untag(u16 ? v[n].w : v[n].y);
                const float s0 = untag(u16 ? v[n].x : v[n].z), s1 = untag(u16 ? v[n].y : v[n].w);
                const float a = k0 + __shfl_xor_sync(0xffffffffu, s0, 16);
                const float b = k1 + __shfl_xor_sync(0xffffffffu, s1, 16);
                const float h = (u8 ? b : a) + __shfl_xor_sync(0xffffffffu, u8 ? a : b, 8);
                stsf(sb + SM_HS + (gw * 144 + ((n == 4 && j >= 4) ? 96 : n * 32) + j * 4 + rg) * 4, h);
            }
            bar_sync(BAR_G, 128);
#pragma unroll 1
            for (int f = lane; f < 144; f += 32)
                sts16(sb + SM_ACT + bv_off(f >> 1, gw) + (f & 1) * 2,
                      __float2bfloat16_rn(mish(ldsf(sb + SM_HS + (gw * 144 + f) * 4) + ldsf(sb + SM_B1 + f * 4))));
            bar_arrive(BAR_ACT, 128 + 288);
            if (gw == 0) TS(6);
        }
        final_reduce(sb, gx, out, ci, cg, gw, lane, tag, epoch, cta == 0 && gw == 0);
        return;
    }

    if (warp >= 9) {
        const int gw = warp - 9;
        {
            mbar_wait(sb + SM_FULL + (QWAIT) * 8);
            const int hh = gw >> 1, rg = lane >> 3, q0 = (gw & 1) * 64 + (lane & 7) * 4;
            const uint32_t* qbase = gx + G_QP + (((2 * hkv + hh) * 4 + rg) * B_ + ab) * DH_ + q0;
            const uint32_t* const pq[2] = {qbase, qbase + 32};
            uint4 vq[2];
            gather_n<2>(pq, vq, tag, 200);
#pragma unroll
            for (int n = 0; n < 2; n++) {
                float a = untag(vq[n].x), b = untag(vq[n].y), c = untag(vq[n].z), d = untag(vq[n].w);
#pragma unroll
                for (int o = 8; o <= 16; o <<= 1) {
                    a += __shfl_xor_sync(0xffffffffu, a, o);
                    b += __shfl_xor_sync(0xffffffffu, b, o);
                    c += __shfl_xor_sync(0xffffffffu, c, o);
                    d += __shfl_xor_sync(0xffffffffu, d, o);
                }
                if (rg == 0) {
                    const uint32_t a_ = sb + SM_Q + bv_off((q0 + n * 32) >> 1, hh);
                    sts32(a_, pack_bf16(a, b));
                    sts32(a_ + 8, pack_bf16(c, d));
                }
            }
            bar_arrive(BAR_Q, 128 + 256);
            if (gw == 0) TS(7);
        }
        if (gw == 0) {
            mbar_wait(sb + SM_FULL + (P_V + 2) * 8);
            const uint32_t* const ps[1] = {gx + G_ST + ((hkv * B_ + ab) * 2 + (asplit ^ (lane & 1))) * 8};
            uint4 vs[1];
            gather_n<1>(ps, vs, tag, 200);
            const int hh = (lane >> 1) & 1;
            const float ms = untag(hh ? vs[0].z : vs[0].x), ls = untag(hh ? vs[0].w : vs[0].y);
            const float mo = __shfl_xor_sync(0xffffffffu, ms, 1), lo = __shfl_xor_sync(0xffffffffu, ls, 1);
            const float m = fmaxf(ms, mo);
            const float es = exp2f(ms - m), eo = exp2f(mo - m);
            if (lane == 0 || lane == 2) stsf(sb + SM_W + hh * 4, es / (ls * es + lo * eo));
            bar_arrive(BAR_W, 32 + 256);
        }
        {
            mbar_wait(sb + SM_FULL + (OWAIT) * 8);
            const int sp = lane >> 4, d0 = (lane & 15) * 4;
            const uint32_t* base = gx + G_OP + ((ci * B_ + gw) * 2 + sp) * DH_ + d0;
            const uint32_t* const p[2] = {base, base + 64};
            uint4 v[2];
            gather_n<2>(p, v, tag, OSLEEP);
            const uint4 keep = sp ? v[1] : v[0], send = sp ? v[0] : v[1];
            const float a = untag(keep.x) + __shfl_xor_sync(0xffffffffu, untag(send.x), 16);
            const float b = untag(keep.y) + __shfl_xor_sync(0xffffffffu, untag(send.y), 16);
            const float c = untag(keep.z) + __shfl_xor_sync(0xffffffffu, untag(send.z), 16);
            const float d = untag(keep.w) + __shfl_xor_sync(0xffffffffu, untag(send.w), 16);
            const uint32_t a_ = sb + SM_O + bv_off((d0 + sp * 64) >> 1, gw);
            sts32(a_, pack_bf16(a, b));
            sts32(a_ + 8, pack_bf16(c, d));
            bar_arrive(BAR_O, 128 + 288);
            if (gw == 0) TS(12);
        }
        return;
    }

    if (warp == 0) TS(3);
    const int lrow = (lane & 7) + ((lane >> 4) << 3);
    const int lchk = (lane >> 3) & 1;
    const uint32_t off_sw = lrow * 128 + ((((warp & 3) * 2 + lchk) ^ (lane & 7)) << 4);
    const uint32_t off_ln = lrow * 288 + (warp * 2 + lchk) * 16;
    const uint32_t bv_lane = (g8 & 3) * 32 + t4 * 8;
    uint32_t* const pub_f = gx + G_FP + ((cg * 32 + ci) * B_ + 2 * t4) * 144 + warp * 16 + g8;
    uint32_t* const pub_h = gx + G_HP + ((ci * 4 + cg) * B_ + 2 * t4) * 144 + warp * 16 + g8;
    uint32_t* const pub_o = gx + G_OP + ((2 * hkv * B_ + ab) * 2 + asplit) * DH_ + warp * 16 + g8;

    if (t4 == 0 && warp < 8) st_pub4(pub_o, B_ * 2 * DH_, 0u, 0u, 0u, 0u);

    if (t4 < 2) st_pub4(pub_f, 144, 0u, 0u, 0u, 0u);

#pragma unroll 1
    for (int phi = 0; phi < 3; phi++) {
        const int ph = phi == 0 ? 0 : 3 - phi;
        const bool wide = ph == 2;
        if (ph == 1 && warp < 8) {
            bar_sync(BAR_Q, 128 + 256);
            uint2 qa[8];
#pragma unroll
            for (int kk = 0; kk < 8; kk++) qa[kk] = lds64(sb + SM_Q + kk * 128 + (g8 & 1) * 32 + t4 * 8);
            const int key = warp * 8 + (lane & 7);
            const uint32_t koff = key * 128;
            const uint32_t kx0 = ((lane >> 3) ^ (key & 7)) << 4, kx1 = (((lane >> 3) + 4) ^ (key & 7)) << 4;
            float mx = -INFINITY;
#pragma unroll 1
            for (int j = 0; j < 8; j++) {
                mbar_wait(sb + SM_FULL + (P_K + j) * 8);
                const uint32_t ka = sb + slot_of(P_K + j) * SLOT + koff;
                float c0[4] = {0.f, 0.f, 0.f, 0.f}, c1[4] = {0.f, 0.f, 0.f, 0.f};
#pragma unroll
                for (int qd = 0; qd < 4; qd++) {
                    uint32_t r0, r1, r2, r3;
                    ldsm_x4(ka + (qd >> 1) * 8192 + ((qd & 1) ? kx1 : kx0), r0, r1, r2, r3);
                    mma16816(c0, qa[2 * qd].x, qa[2 * qd].x, qa[2 * qd].y, qa[2 * qd].y, r0, r1);
                    mma16816(c1, qa[2 * qd + 1].x, qa[2 * qd + 1].x, qa[2 * qd + 1].y, qa[2 * qd + 1].y, r2, r3);
                }
                __syncwarp();
                if (lane == 0) mbar_arrive(sb + SM_EMPTY + (P_K + j) * 8);
                const float s0 = c0[0] + c1[0], s1 = c0[1] + c1[1];
                mx = fmaxf(mx, fmaxf(s0, s1));
                if (g8 < 2) sts64f(sb + SM_SC + (((4 * j + (warp >> 1)) * 2 + g8) * 8 + t4 * 2 + (warp & 1)) * 8, s0, s1);
            }
            if (warp == 0) TS(8);
            mx = fmaxf(mx, __shfl_xor_sync(0xffffffffu, mx, 1));
            mx = fmaxf(mx, __shfl_xor_sync(0xffffffffu, mx, 2));
            if (g8 < 2 && t4 == 0) stsf(sb + SM_RED + (warp * 2 + g8) * 4, mx);
            bar_sync(BAR_CMP, 256);
            const float kScale = 0.08838834764831845f * 1.4426950408889634f;
            const int hh = (tid >> 3) & 1;
            float m = ldsf(sb + SM_RED + ((lane & 7) * 2 + hh) * 4);
            m = fmaxf(m, __shfl_xor_sync(0xffffffffu, m, 1));
            m = fmaxf(m, __shfl_xor_sync(0xffffffffu, m, 2));
            m = fmaxf(m, __shfl_xor_sync(0xffffffffu, m, 4));
            m = untag(__float_as_uint(m * kScale));
            float l = 0.f;
#pragma unroll
            for (int n = 0; n < 2; n++) {
                const int idx = tid + n * 256;
                const uint2 s = lds64(sb + SM_SC + idx * 8);
                const float p0 = exp2f(fmaf(__uint_as_float(s.x), kScale, -m));
                const float p1 = exp2f(fmaf(__uint_as_float(s.y), kScale, -m));
                l += p0 + p1;
                sts32(sb + SM_P + ((idx >> 4) * 32 + (idx & 15)) * 4, pack_bf16(p0, p1));
            }
            l += __shfl_xor_sync(0xffffffffu, l, 1);
            l += __shfl_xor_sync(0xffffffffu, l, 2);
            l += __shfl_xor_sync(0xffffffffu, l, 4);
            l += __shfl_xor_sync(0xffffffffu, l, 16);
            if (lane < 16 && (lane & 7) == 0) stsf(sb + SM_RED + (16 + warp * 2 + hh) * 4, l);
            bar_sync(BAR_CMP, 256);
            if (warp == 0) {
                float ls = ldsf(sb + SM_RED + (16 + (lane & 7) * 2 + hh) * 4);
                ls += __shfl_xor_sync(0xffffffffu, ls, 1);
                ls += __shfl_xor_sync(0xffffffffu, ls, 2);
                ls += __shfl_xor_sync(0xffffffffu, ls, 4);
                if ((lane & 6) == 0)
                    st_pub(gx + G_ST + ((hkv * B_ + ab) * 2 + asplit) * 8 + (lane >> 4) * 4 + hh * 2 + (lane & 1),
                           tagw((lane & 1) ? ls : m, tag));
                TS(9);
            }
        }
        if (wide || warp < 8) {
            const int p0 = ph == 0 ? P_WQ : ph == 1 ? P_V : P_W1;
            const int np = ph == 1 ? 8 : 3;
            const int kpp = ph == 1 ? 4 : 3;
            const uint32_t aoff = wide ? off_ln : off_sw + (warp >> 2) * (ph == 0 ? 6144 : 8192);
            const uint32_t kstr = wide ? 16 * 288 : 16 * 128;
            uint32_t bv = sb + bv_lane + (ph == 1 ? SM_P : SM_XN);
            float acc[4] = {0.f, 0.f, 0.f, 0.f}, acd[4] = {0.f, 0.f, 0.f, 0.f};
#pragma unroll 1
            for (int p = p0; p < p0 + np; p++) {
                uint2 b[4];
#pragma unroll
                for (int ks = 0; ks < 4; ks++) b[ks] = lds64(bv + ks * 128);
                mbar_wait(sb + SM_FULL + p * 8);
                const uint32_t aa = sb + slot_of(p) * SLOT + aoff;
                uint32_t a[4][4];
#pragma unroll
                for (int ks = 0; ks < 4; ks++)
                    if (ks < 3 || kpp == 4) ldsm_x4_t(aa + ks * kstr, a[ks][0], a[ks][1], a[ks][2], a[ks][3]);
                mma16816(acc, a[0][0], a[0][1], a[0][2], a[0][3], b[0].x, b[0].y);
                mma16816(acd, a[1][0], a[1][1], a[1][2], a[1][3], b[1].x, b[1].y);
                mma16816(acc, a[2][0], a[2][1], a[2][2], a[2][3], b[2].x, b[2].y);
                if (kpp == 4) mma16816(acd, a[3][0], a[3][1], a[3][2], a[3][3], b[3].x, b[3].y);
                bv += kpp * 128;
                __syncwarp();
                if (lane == 0 && p < NEMPTY) mbar_arrive(sb + SM_EMPTY + p * 8);
                if (ph == 1 && p == p0 + np - 2) bar_sync(BAR_W, 32 + 256);
            }
            float w0 = 1.f, w1 = 1.f;
            if (ph == 1) { w0 = ldsf(sb + SM_W); w1 = ldsf(sb + SM_W + 4); }
            uint32_t* d0 = ph == 0 ? gx + G_QP + ((ci * 4 + cg) * B_ + 2 * t4) * DH_ + warp * 16 + g8
                         : ph == 1 ? pub_o : pub_h;
            if (t4 < (ph == 1 ? 1 : 2))
                st_pub4(d0, ph == 0 ? DH_ : ph == 1 ? B_ * 2 * DH_ : 144, tagw((acc[0] + acd[0]) * w0, tag),
                        tagw((acc[1] + acd[1]) * w1, tag), tagw((acc[2] + acd[2]) * w0, tag),
                        tagw((acc[3] + acd[3]) * w1, tag));
        }
        if (warp == 0) TS(ph == 0 ? 4 : ph == 1 ? 10 : 5);
    }

    {
        float c0[4] = {0.f, 0.f, 0.f, 0.f}, c1[4] = {0.f, 0.f, 0.f, 0.f};
        bar_sync(BAR_ACT, 128 + 288);
#pragma unroll
        for (int p = 0; p < 3; p++) {
            mbar_wait(sb + SM_FULL + (P_W2 + p) * 8);
#pragma unroll
            for (int ks = 0; ks < 3; ks++) {
                uint32_t a0, a1, a2, a3;
                ldsm_x4_t(sb + slot_of(P_W2 + p) * SLOT + off_ln + ks * 16 * 288, a0, a1, a2, a3);
                const uint2 b = lds64(sb + bv_lane + SM_ACT + (p * 3 + ks) * 128);
                if (ks & 1) mma16816(c1, a0, a1, a2, a3, b.x, b.y);
                else mma16816(c0, a0, a1, a2, a3, b.x, b.y);
            }
        }
        if (warp == 0) TS(11);
        uint32_t a[6][4];
#pragma unroll
        for (int p = 0; p < 3; p++) {
            mbar_wait(sb + SM_FULL + (P_WO + p) * 8);
#pragma unroll
            for (int ks = 0; ks < 2; ks++)
                ldsm_x4_t(sb + slot_of(P_WO + p) * SLOT + off_ln + ks * 16 * 288,
                          a[2 * p + ks][0], a[2 * p + ks][1], a[2 * p + ks][2], a[2 * p + ks][3]);
        }
        if (warp == 0) TS(17);
        bar_sync(BAR_O, 128 + 288);
        uint2 b[8];
#pragma unroll
        for (int k = 0; k < 8; k++) b[k] = lds64(sb + bv_lane + SM_O + k * 128);
#pragma unroll
        for (int k = 0; k < 6; k++) {
            if (k & 1) mma16816(c1, a[k][0], a[k][1], a[k][2], a[k][3], b[k].x, b[k].y);
            else mma16816(c0, a[k][0], a[k][1], a[k][2], a[k][3], b[k].x, b[k].y);
        }
        if (warp == 0) TS(16);
        mbar_wait(sb + SM_FULL + (P_WO + 3) * 8);
        if (warp == 0) TS(20);
        ldsm_x4_t(sb + slot_of(P_WO + 3) * SLOT + off_ln, a[0][0], a[0][1], a[0][2], a[0][3]);
        ldsm_x4_t(sb + slot_of(P_WO + 3) * SLOT + off_ln + 16 * 288, a[1][0], a[1][1], a[1][2], a[1][3]);
        mma16816(c0, a[0][0], a[0][1], a[0][2], a[0][3], b[6].x, b[6].y);
        mma16816(c1, a[1][0], a[1][1], a[1][2], a[1][3], b[7].x, b[7].y);
        if (t4 < 2)
            st_pub4(pub_f, 144, tagw(c0[0] + c1[0], tag), tagw(c0[1] + c1[1], tag), tagw(c0[2] + c1[2], tag),
                    tagw(c0[3] + c1[3], tag));
        __syncwarp();
        if (lane == 0) mbar_arrive(sb + SM_DONE);
        if (warp == 0) TS(13);
        TS(21 + warp);
    }
}

typedef CUresult (*EncodeTiledFn)(CUtensorMap*, CUtensorMapDataType, cuuint32_t, void*, const cuuint64_t*,
                                  const cuuint64_t*, const cuuint32_t*, const cuuint32_t*, CUtensorMapInterleave,
                                  CUtensorMapSwizzle, CUtensorMapL2promotion, CUtensorMapFloatOOBfill);

void make_map_lin(EncodeTiledFn fn, CUtensorMap* tm, const void* ptr, uint64_t cols, uint64_t rows, uint32_t box_rows) {
    cuuint64_t gdim[3] = {cols, rows, 1};
    cuuint64_t gstr[2] = {cols * 2, cols * rows * 2};
    cuuint32_t box[3] = {144, box_rows, 1};
    cuuint32_t estr[3] = {1, 1, 1};
    fn(tm, CU_TENSOR_MAP_DATA_TYPE_BFLOAT16, 3, const_cast<void*>(ptr), gdim, gstr, box, estr,
       CU_TENSOR_MAP_INTERLEAVE_NONE, CU_TENSOR_MAP_SWIZZLE_NONE, CU_TENSOR_MAP_L2_PROMOTION_L2_256B,
       CU_TENSOR_MAP_FLOAT_OOB_FILL_NONE);
}
void make_map_sw(EncodeTiledFn fn, CUtensorMap* tm, const void* ptr, uint64_t cols, uint64_t rows, uint32_t box_rows) {
    cuuint64_t gdim[3] = {64, rows, cols / 64};
    cuuint64_t gstr[2] = {cols * 2, 128};
    cuuint32_t box[3] = {64, box_rows, 2};
    cuuint32_t estr[3] = {1, 1, 1};
    fn(tm, CU_TENSOR_MAP_DATA_TYPE_BFLOAT16, 3, const_cast<void*>(ptr), gdim, gstr, box, estr,
       CU_TENSOR_MAP_INTERLEAVE_NONE, CU_TENSOR_MAP_SWIZZLE_128B, CU_TENSOR_MAP_L2_PROMOTION_L2_256B,
       CU_TENSOR_MAP_FLOAT_OOB_FILL_NONE);
}

}

extern "C" void kernel_launch(void* const* d_in, const int* in_sizes, int n_in, void* d_out, int out_size) {
    (void)in_sizes; (void)n_in; (void)out_size;
    static EncodeTiledFn encode = nullptr;
    if (!encode) {
        void* fn = nullptr;
        cudaDriverEntryPointQueryResult st;
        cudaGetDriverEntryPoint("cuTensorMapEncodeTiled", &fn, cudaEnableDefault, &st);
        encode = (EncodeTiledFn)fn;
        cudaFuncSetAttribute(fused_decode_kernel, cudaFuncAttributeMaxDynamicSharedMemorySize, SMEM_BYTES);
    }
    Maps maps;
    make_map_sw(encode, &maps.m[0], d_in[3], HQ_ * DH_, D_, 48);
    make_map_sw(encode, &maps.m[1], d_in[1], DH_, (uint64_t)B_ * HKV_ * SK_, 64);
    make_map_sw(encode, &maps.m[2], d_in[2], DH_, (uint64_t)B_ * HKV_ * SK_, 64);
    make_map_lin(encode, &maps.m[3], d_in[6], F_, D_, 48);
    make_map_lin(encode, &maps.m[4], d_in[8], D_, F_, 48);
    make_map_lin(encode, &maps.m[5], d_in[4], D_, HQ_ * DH_, 32);
    fused_decode_kernel<<<NCTA, NTHREADS, SMEM_BYTES>>>(maps, (const __nv_bfloat16*)d_in[0],
                                                        (const __nv_bfloat16*)d_in[7], (__nv_bfloat16*)d_out);
}
```

```cpp
#include <cuda_runtime.h>
#include <cuda_bf16.h>
#include <cuda.h>
#include <stdint.h>

namespace {

constexpr int D_ = 576, HQ_ = 32, HKV_ = 16, SK_ = 4096, DH_ = 128, W_ = 1024, F_ = 4608, B_ = 4;
constexpr int NCTA = 128;
constexpr int PROD_WARP = 17;
constexpr int NTHREADS = 576;
#define DMIN 2
#define DMAX 6
#define PRATE 25.25f
#define PW0 26.f
#define PT0 400.f
#define OWAIT (P_W2)
#define PW1 36.f
#define QSW 25
#define NFIRST 3
#define QWAIT (P_K + 2)
#define OSLEEP 200
#define FSLEEP 200
constexpr int SLOT = 16384;
constexpr int NSLOT = 13;
constexpr int P_WQ = 0, P_W1 = 3, P_K = 6, P_V = 14, P_W2 = 22, P_WO = 25, NPIECE = 29;
constexpr int NEMPTY = NPIECE - NSLOT;

constexpr int SM_XN = NSLOT * SLOT;
constexpr int SM_ACT = SM_XN + 9 * 128;
constexpr int SM_O = SM_ACT + 9 * 128;
constexpr int SM_Q = SM_O + 8 * 128;
constexpr int SM_P = SM_Q + 8 * 128;
constexpr int SM_SC = SM_P + 32 * 128;
constexpr int SM_X = SM_SC + 512 * 8;
constexpr int SM_B1 = SM_X + 4 * 144 * 4;
constexpr int SM_HS = SM_B1 + 144 * 4;
constexpr int SM_RED = SM_HS + 4 * 144 * 4;
constexpr int SM_W = SM_RED + 32 * 4;
constexpr int SM_FULL = SM_W + 8;
constexpr int SM_EMPTY = SM_FULL + NPIECE * 8;
constexpr int SM_DONE = SM_EMPTY + NEMPTY * 8;
constexpr int SM_TAG = SM_DONE + 8;
constexpr int SM_TOTAL = SM_TAG + 16;
constexpr int SMEM_BYTES = SM_TOTAL + 1024;

constexpr unsigned SPIN_LIMIT = 1u << 21;

constexpr int BAR_CMP = 1;
constexpr int BAR_Q = 2;
constexpr int BAR_ACT = 3;
constexpr int BAR_O = 4;
constexpr int BAR_INIT = 5;
constexpr int BAR_G = 6;
constexpr int BAR_W = 7;

constexpr int G_QP = 0;
constexpr int G_HP = G_QP + HQ_ * 4 * B_ * DH_;
constexpr int G_OP = G_HP + 32 * 4 * B_ * 144;
constexpr int G_ST = G_OP + HQ_ * B_ * 2 * DH_;
constexpr int G_FP = G_ST + HKV_ * B_ * 2 * 8;
constexpr int G_EPOCH = G_FP + 4 * 32 * B_ * 144;
__device__ __align__(256) uint32_t g_x[G_EPOCH + 64];

#define TS(idx) do {} while (0)
#define TSA(idx) do {} while (0)
#define TSG(idx) do {} while (0)

__device__ __forceinline__ uint32_t smem_u32(const void* p) { return (uint32_t)__cvta_generic_to_shared(p); }
__device__ __forceinline__ void mbar_init(uint32_t bar, uint32_t cnt) {
    asm volatile("mbarrier.init.shared::cta.b64 [%0], %1;" ::"r"(bar), "r"(cnt) : "memory");
}
__device__ __forceinline__ void mbar_expect_tx(uint32_t bar, uint32_t bytes) {
    asm volatile("mbarrier.arrive.expect_tx.shared::cta.b64 _, [%0], %1;" ::"r"(bar), "r"(bytes) : "memory");
}
__device__ __forceinline__ void mbar_arrive(uint32_t bar) {
    asm volatile("mbarrier.arrive.shared::cta.b64 _, [%0];" ::"r"(bar) : "memory");
}
__device__ __forceinline__ bool mbar_test(uint32_t bar) {
    uint32_t ok;
    asm volatile(
        "{\n.reg .pred p;\n"
        "mbarrier.test_wait.parity.shared::cta.b64 p, [%1], 0;\n"
        "selp.u32 %0, 1, 0, p;\n}"
        : "=r"(ok) : "r"(bar) : "memory");
    return ok != 0;
}
__device__ __forceinline__ void mbar_wait(uint32_t bar) {
    asm volatile(
        "{\n.reg .pred p;\n.reg .u32 c;\n"
        "mov.u32 c, 0;\n"
        "W_%=:\n"
        "mbarrier.try_wait.parity.shared::cta.b64 p, [%0], 0;\n"
        "@p bra D_%=;\n"
        "add.u32 c, c, 1;\n"
        "setp.lt.u32 p, c, %1;\n"
        "@p bra W_%=;\n"
        "D_%=:\n}"
        ::"r"(bar), "n"(SPIN_LIMIT) : "memory");
}
__device__ __forceinline__ void tma_3d(uint32_t dst, const CUtensorMap* tm, int c0, int c1, int c2, uint32_t bar) {
    uint64_t pol;
    asm volatile("createpolicy.fractional.L2::evict_first.b64 %0, 1.0;" : "=l"(pol));
    asm volatile(
        "cp.async.bulk.tensor.3d.shared::cluster.global.mbarrier::complete_tx::bytes.L2::cache_hint"
        " [%0], [%1, {%3, %4, %5}], [%2], %6;"
        ::"r"(dst), "l"(tm), "r"(bar), "r"(c0), "r"(c1), "r"(c2), "l"(pol) : "memory");
}
__device__ __forceinline__ void prefetch_tm(const CUtensorMap* tm) {
    asm volatile("prefetch.tensormap [%0];" ::"l"(tm) : "memory");
}
__device__ __forceinline__ void ldsm_x4(uint32_t addr, uint32_t& r0, uint32_t& r1, uint32_t& r2, uint32_t& r3) {
    asm volatile("ldmatrix.sync.aligned.m8n8.x4.shared.b16 {%0,%1,%2,%3}, [%4];"
                 : "=r"(r0), "=r"(r1), "=r"(r2), "=r"(r3) : "r"(addr) : "memory");
}
__device__ __forceinline__ void ldsm_x4_t(uint32_t addr, uint32_t& r0, uint32_t& r1, uint32_t& r2, uint32_t& r3) {
    asm volatile("ldmatrix.sync.aligned.m8n8.x4.trans.shared.b16 {%0,%1,%2,%3}, [%4];"
                 : "=r"(r0), "=r"(r1), "=r"(r2), "=r"(r3) : "r"(addr) : "memory");
}
__device__ __forceinline__ void mma16816(float (&c)[4], uint32_t a0, uint32_t a1, uint32_t a2, uint32_t a3,
                                         uint32_t b0, uint32_t b1) {
    asm volatile(
        "mma.sync.aligned.m16n8k16.row.col.f32.bf16.bf16.f32 {%0,%1,%2,%3}, {%4,%5,%6,%7}, {%8,%9}, {%0,%1,%2,%3};"
        : "+f"(c[0]), "+f"(c[1]), "+f"(c[2]), "+f"(c[3])
        : "r"(a0), "r"(a1), "r"(a2), "r"(a3), "r"(b0), "r"(b1));
}
__device__ __forceinline__ void bar_sync(int id, int nthreads) {
    asm volatile("bar.sync %0, %1;" ::"r"(id), "r"(nthreads) : "memory");
}
__device__ __forceinline__ void bar_arrive(int id, int nthreads) {
    asm volatile("bar.arrive %0, %1;" ::"r"(id), "r"(nthreads) : "memory");
}
__device__ __forceinline__ uint2 lds64(uint32_t a) {
    uint2 v; asm volatile("ld.shared.v2.u32 {%0,%1}, [%2];" : "=r"(v.x), "=r"(v.y) : "r"(a) : "memory"); return v;
}
__device__ __forceinline__ float ldsf(uint32_t a) {
    float v; asm volatile("ld.shared.f32 %0, [%1];" : "=f"(v) : "r"(a) : "memory"); return v;
}
__device__ __forceinline__ void sts32(uint32_t a, uint32_t v) {
    asm volatile("st.shared.u32 [%0], %1;" ::"r"(a), "r"(v) : "memory");
}
__device__ __forceinline__ void stsf(uint32_t a, float v) {
    asm volatile("st.shared.f32 [%0], %1;" ::"r"(a), "f"(v) : "memory");
}
__device__ __forceinline__ void sts64f(uint32_t a, float v0, float v1) {
    asm volatile("st.shared.v2.f32 [%0], {%1,%2};" ::"r"(a), "f"(v0), "f"(v1) : "memory");
}
__device__ __forceinline__ void sts16(uint32_t a, __nv_bfloat16 v) {
    asm volatile("st.shared.u16 [%0], %1;" ::"r"(a), "h"(__bfloat16_as_ushort(v)) : "memory");
}
__device__ __forceinline__ uint32_t tagw(float v, uint32_t tag) { return (__float_as_uint(v) & ~15u) | tag; }
__device__ __forceinline__ void st_pub(uint32_t* p, uint32_t v) {
    asm volatile("st.relaxed.gpu.global.u32 [%0], %1;" ::"l"(p), "r"(v) : "memory");
}
__device__ __forceinline__ void st_pub4(uint32_t* d0, int S, uint32_t w0, uint32_t w1, uint32_t w2, uint32_t w3) {
    st_pub(d0, w0); st_pub(d0 + S, w1); st_pub(d0 + 8, w2); st_pub(d0 + S + 8, w3);
}
__device__ __forceinline__ uint4 ld_poll(const uint32_t* p) {
    uint4 v;
    asm volatile("ld.relaxed.gpu.global.v4.u32 {%0,%1,%2,%3}, [%4];"
                 : "=r"(v.x), "=r"(v.y), "=r"(v.z), "=r"(v.w) : "l"(p) : "memory");
    return v;
}
__device__ __forceinline__ bool tag_ok(const uint4& v, uint32_t tag) {
    return ((((v.x ^ tag) | (v.y ^ tag)) | ((v.z ^ tag) | (v.w ^ tag))) & 15u) == 0;
}
template <int N>
__device__ __forceinline__ void gather_n(const uint32_t* const (&p)[N], uint4 (&v)[N], uint32_t tag, unsigned sleep_ns) {
#pragma unroll
    for (int n = 0; n < N; n++) v[n] = make_uint4(0, 0, 0, 0);
    unsigned it = 0;
#pragma unroll 1
    while (true) {
#pragma unroll
        for (int n = 0; n < N; n++)
            if (!tag_ok(v[n], tag)) v[n] = ld_poll(p[n]);
        bool ok = true;
#pragma unroll
        for (int n = 0; n < N; n++) ok = ok && tag_ok(v[n], tag);
        if (ok || ++it > SPIN_LIMIT) break;
        __nanosleep(sleep_ns);
    }
    __syncwarp();
}
__device__ __forceinline__ float untag(uint32_t w) { return __uint_as_float(w & ~15u); }
__device__ __forceinline__ float bf16r(float v) { return __bfloat162float(__float2bfloat16_rn(v)); }
__device__ __forceinline__ uint32_t pack_bf16(float lo, float hi) {
    __nv_bfloat162 h = __floats2bfloat162_rn(lo, hi);
    return *reinterpret_cast<uint32_t*>(&h);
}
__device__ __forceinline__ uint32_t bv_off(int e2, int n) {
    return ((e2 >> 3) * 32 + n * 8 + (e2 & 3) * 2 + ((e2 >> 2) & 1)) * 4;
}
__device__ __forceinline__ float mish(float h) {
    const float e = __expf(fminf(h, 30.f));
    const float n = e * (e + 2.f);
    return h * __fdividef(n, n + 2.f);
}
__device__ __forceinline__ int slot_of(int p) { return p < NSLOT ? p : (p < 2 * NSLOT ? p - NSLOT : p - 2 * NSLOT); }

__device__ __forceinline__ void final_reduce(uint32_t sb, uint32_t* gx, __nv_bfloat16* out, int ci, int cg, int gw, int lane,
                                             uint32_t tag, unsigned epoch, bool bump_epoch) {
    const int task = ci + 32 * gw;
    if (task >= 72) return;
    const int tb = task / 18, tc = (task % 18) * 8;
    const uint32_t* fbase = gx + G_FP + ((cg * 32 + (lane >> 1)) * B_ + tb) * 144 + tc + (lane & 1) * 4;
    const int ocol = tc + (lane & 1) * 4 + ((lane >> 4) & 1) * 2 + ((lane >> 3) & 1);
    const float xv = ldsf(sb + SM_X + (tb * 144 + ocol) * 4);
    uint4 v0 = make_uint4(0, 0, 0, 0), v1 = v0;
    mbar_wait(sb + SM_FULL + (P_WO + 2) * 8);
    unsigned it = 0;
#pragma unroll 1
    while (true) {
        if (!tag_ok(v0, tag)) v0 = ld_poll(fbase);
        if (!tag_ok(v1, tag)) v1 = ld_poll(fbase + 16 * B_ * 144);
        if ((tag_ok(v0, tag) && tag_ok(v1, tag)) || ++it > SPIN_LIMIT) break;
        if (!mbar_test(sb + SM_DONE)) __nanosleep(FSLEEP);
    }
    __syncwarp();
    const float r0 = untag(v0.x) + untag(v1.x), r1 = untag(v0.y) + untag(v1.y);
    const float r2 = untag(v0.z) + untag(v1.z), r3 = untag(v0.w) + untag(v1.w);
    const bool u16 = lane & 16, u8 = lane & 8;
    const float sa = (u16 ? r2 : r0) + __shfl_xor_sync(0xffffffffu, u16 ? r0 : r2, 16);
    const float sc = (u16 ? r3 : r1) + __shfl_xor_sync(0xffffffffu, u16 ? r1 : r3, 16);
    float s1 = (u8 ? sc : sa) + __shfl_xor_sync(0xffffffffu, u8 ? sa : sc, 8);
    s1 += __shfl_xor_sync(0xffffffffu, s1, 4);
    s1 += __shfl_xor_sync(0xffffffffu, s1, 2);
    if ((lane & 6) == 0) out[tb * D_ + cg * 144 + ocol] = __float2bfloat16_rn(xv + s1);
    if (bump_epoch && lane == 0) {
        st_pub(gx + G_EPOCH, tag % 15u);
    }
    if (gw == 0) TS(14);
}

struct Maps { CUtensorMap m[6]; };

__global__ void __launch_bounds__(NTHREADS, 1)
fused_decode_kernel(const __grid_constant__ Maps maps, const __nv_bfloat16* __restrict__ x,
                    const __nv_bfloat16* __restrict__ b1, __nv_bfloat16* __restrict__ out) {
    extern __shared__ unsigned char smem_raw[];
    const uint32_t sb = (smem_u32(smem_raw) + 1023u) & ~1023u;

    const int tid = threadIdx.x, warp = tid >> 5, lane = tid & 31;
    const int cta = blockIdx.x;
    const int ci = cta >> 2, cg = cta & 3;
    const int hkv = ci >> 1;
    const int bs = ((ci & 1) << 2) | cg;
    const int ab = bs >> 1, asplit = bs & 1;
    const int kv_row0 = (ab * HKV_ + hkv) * SK_ + (SK_ - W_) + asplit * 512;

    unsigned t_start = 0;
    if (tid == PROD_WARP * 32) {
        TSA(0);
#pragma unroll
        for (int p = 0; p < NFIRST; p++) mbar_init(sb + SM_FULL + p * 8, 1);
        asm volatile("fence.mbarrier_init.release.cluster;" ::: "memory");
#pragma unroll
        for (int p = 0; p < (NFIRST < 3 ? NFIRST : 3); p++) {
            mbar_expect_tx(sb + SM_FULL + p * 8, 48 * 256);
            tma_3d(sb + p * SLOT, &maps.m[0], 0, cg * 144 + p * 48, 2 * ci, sb + SM_FULL + p * 8);
        }
#pragma unroll
        for (int p = 3; p < NFIRST; p++) {
            mbar_expect_tx(sb + SM_FULL + p * 8, 48 * 288);
            tma_3d(sb + p * SLOT, &maps.m[3], ci * 144, cg * 144 + (p - 3) * 48, 0, sb + SM_FULL + p * 8);
        }
        asm volatile("mov.u32 %0, %%globaltimer_lo;" : "=r"(t_start));
        TSA(1);
    }

    if (warp == PROD_WARP) {
        const int p = lane;
        int mi, c0 = 0, c1, c2 = 0, bytes = 48 * 288;
        float kb;
        if (p < P_W1)      { mi = 0; c1 = cg * 144 + p * 48; c2 = 2 * ci; bytes = 48 * 256; kb = 12.f * p; }
        else if (p < P_K)  { mi = 3; c0 = ci * 144; c1 = cg * 144 + (p - P_W1) * 48; kb = 36.f + 13.5f * (p - P_W1); }
        else if (p < P_V)  { mi = 1; c1 = kv_row0 + (p - P_K) * 64; bytes = 16384; kb = 76.5f + 16.f * (p - P_K); }
        else if (p < P_W2) { mi = 2; c1 = kv_row0 + (p - P_V) * 64; bytes = 16384; kb = 76.5f + 16.f * (p - P_K); }
        else if (p < P_WO) { mi = 4; c0 = cg * 144; c1 = ci * 144 + (p - P_W2) * 48; kb = 332.5f + 13.5f * (p - P_W2); }
        else { mi = 5; c0 = cg * 144; c1 = ci * 128 + (p - P_WO) * 32; bytes = 32 * 288; kb = 373.f + 9.f * (p - P_WO); }
        const uint32_t fb = sb + SM_FULL + p * 8;
        if (p >= 1 && p < 6) prefetch_tm(&maps.m[p]);
        if (lane == 0) {
#pragma unroll
            for (int q = NFIRST; q < NPIECE; q++) mbar_init(sb + SM_FULL + q * 8, 1);
#pragma unroll
            for (int e = 0; e <= NEMPTY; e++) mbar_init(sb + SM_EMPTY + e * 8, (e == NEMPTY || (e >= P_W1 && e < P_W1 + 3)) ? 9 : 8);
            asm volatile("fence.mbarrier_init.release.cluster;" ::: "memory");
        }
        __syncwarp();
        bar_arrive(BAR_INIT, NTHREADS);
        const unsigned t_issue = __shfl_sync(0xffffffffu, t_start, 0) + (unsigned)(int)(PT0 + (kb - (p < QSW ? PW0 : PW1)) * (1000.f / PRATE));
#pragma unroll 1
        for (int q = NFIRST; q < NPIECE; q++) {
            if (lane == q) {
                if (q >= DMAX) mbar_wait(fb - DMAX * 8);
                unsigned it = 0;
                while (!mbar_test(fb - min(DMIN, q) * 8) && ++it < SPIN_LIMIT) {
                    unsigned now;
                    asm volatile("mov.u32 %0, %%globaltimer_lo;" : "=r"(now));
                    if ((int)(now - t_issue) >= 0) break;
                }
                if (q >= NSLOT) mbar_wait(sb + SM_EMPTY + (q - NSLOT) * 8);
                mbar_expect_tx(fb, bytes);
                tma_3d(sb + slot_of(p) * SLOT, &maps.m[mi], c0, c1, c2, fb);
            }
            __syncwarp();
        }
        TS(2);
        return;
    }

    const int g8 = lane >> 2, t4 = lane & 3;
    uint32_t* const gx = g_x;

    if (warp < 4) {
        const uint32_t* xw = reinterpret_cast<const uint32_t*>(x + warp * D_);
        uint32_t w[9];
#pragma unroll
        for (int j = 0; j < 9; j++) w[j] = __ldg(xw + lane + 32 * j);
        uint32_t us[3];
#pragma unroll
        for (int j = 0; j < 3; j++) us[j] = __ldg(xw + cg * 72 + min(lane + 32 * j, 71));
        float s = 0.f;
#pragma unroll
        for (int j = 0; j < 9; j++) s += __uint_as_float(w[j] << 16) + __uint_as_float(w[j] & 0xffff0000u);
#pragma unroll
        for (int o = 16; o > 0; o >>= 1) s += __shfl_xor_sync(0xffffffffu, s, o);
        const float mean = s * (1.0f / D_);
        float q = 0.f;
#pragma unroll
        for (int j = 0; j < 9; j++) {
            const float d0 = __uint_as_float(w[j] << 16) - mean, d1 = __uint_as_float(w[j] & 0xffff0000u) - mean;
            q += d0 * d0 + d1 * d1;
        }
#pragma unroll
        for (int o = 16; o > 0; o >>= 1) q += __shfl_xor_sync(0xffffffffu, q, o);
        const float mb = bf16r(mean);
        const float rden = __frcp_rn(bf16r(__fsqrt_rn(bf16r(bf16r(q * (1.0f / D_)) + 1e-5f))));
#pragma unroll
        for (int j = 0; j < 3; j++) {
            const int e2 = min(lane + 32 * j, 71);
            const float v0 = __uint_as_float(us[j] << 16), v1 = __uint_as_float(us[j] & 0xffff0000u);
            sts32(sb + SM_XN + bv_off(e2, warp), pack_bf16(bf16r(v0 - mb) * rden, bf16r(v1 - mb) * rden));
            sts64f(sb + SM_X + (warp * 144 + 2 * e2) * 4, v0, v1);
        }
    } else if (warp == 4) {
        if (lane == 0) {
            unsigned e;
            asm volatile("ld.relaxed.gpu.global.u32 %0, [%1];" : "=r"(e) : "l"(gx + G_EPOCH) : "memory");
            sts32(sb + SM_TAG, e);
        }
    }
    bar_sync(BAR_INIT, NTHREADS);
    const unsigned epoch = __float_as_uint(ldsf(sb + SM_TAG));
    const uint32_t tag = epoch % 15u + 1u;

    if (warp >= 13) {
        const int gw = warp - 13;
        {
            const int e2 = gw * 32 + lane;
            if (e2 < 72) {
                const uint32_t u = __ldg(reinterpret_cast<const uint32_t*>(b1 + ci * 144) + e2);
                sts64f(sb + SM_B1 + e2 * 8, __uint_as_float(u << 16), __uint_as_float(u & 0xffff0000u));
            }
        }
        {
            mbar_wait(sb + SM_FULL + (P_K + 7) * 8);
            const int rg = lane >> 3, j = lane & 7;
            const uint32_t* base = gx + G_HP + ((ci * 4 + rg) * B_ + gw) * 144 + j * 4;
            const uint32_t* const p[5] = {base, base + 32, base + 64, base + 96, base + (j < 4 ? 128 : 96)};
            uint4 v[5];
            gather_n<5>(p, v, tag, 300);
#pragma unroll
            for (int n = 0; n < 5; n++) {
                const bool u16 = lane & 16, u8 = lane & 8;
                const float k0 = untag(u16 ? v[n].z : v[n].x), k1 = untag(u16 ? v[n].w : v[n].y);
                const float s0 = untag(u16 ? v[n].x : v[n].z), s1 = untag(u16 ? v[n].y : v[n].w);
                const float a = k0 + __shfl_xor_sync(0xffffffffu, s0, 16);
                const float b = k1 + __shfl_xor_sync(0xffffffffu, s1, 16);
                const float h = (u8 ? b : a) + __shfl_xor_sync(0xffffffffu, u8 ? a : b, 8);
                stsf(sb + SM_HS + (gw * 144 + ((n == 4 && j >= 4) ? 96 : n * 32) + j * 4 + rg) * 4, h);
            }
            bar_sync(BAR_G, 128);
#pragma unroll 1
            for (int f = lane; f < 144; f += 32)
                sts16(sb + SM_ACT + bv_off(f >> 1, gw) + (f & 1) * 2,
                      __float2bfloat16_rn(mish(ldsf(sb + SM_HS + (gw * 144 + f) * 4) + ldsf(sb + SM_B1 + f * 4))));
            bar_arrive(BAR_ACT, 128 + 288);
            if (gw == 0) TS(6);
        }
        final_reduce(sb, gx, out, ci, cg, gw, lane, tag, epoch, cta == 0 && gw == 0);
        return;
    }

    if (warp >= 9) {
        const int gw = warp - 9;
        {
            mbar_wait(sb + SM_FULL + (QWAIT) * 8);
            const int hh = gw >> 1, rg = lane >> 3, q0 = (gw & 1) * 64 + (lane & 7) * 4;
            const uint32_t* qbase = gx + G_QP + (((2 * hkv + hh) * 4 + rg) * B_ + ab) * DH_ + q0;
            const uint32_t* const pq[2] = {qbase, qbase + 32};
            uint4 vq[2];
            gather_n<2>(pq, vq, tag, 200);
#pragma unroll
            for (int n = 0; n < 2; n++) {
                float a = untag(vq[n].x), b = untag(vq[n].y), c = untag(vq[n].z), d = untag(vq[n].w);
#pragma unroll
                for (int o = 8; o <= 16; o <<= 1) {
                    a += __shfl_xor_sync(0xffffffffu, a, o);
                    b += __shfl_xor_sync(0xffffffffu, b, o);
                    c += __shfl_xor_sync(0xffffffffu, c, o);
                    d += __shfl_xor_sync(0xffffffffu, d, o);
                }
                if (rg == 0) {
                    const uint32_t a_ = sb + SM_Q + bv_off((q0 + n * 32) >> 1, hh);
                    sts32(a_, pack_bf16(a, b));
                    sts32(a_ + 8, pack_bf16(c, d));
                }
            }
            bar_arrive(BAR_Q, 128 + 256);
            if (gw == 0) TS(7);
        }
        if (gw == 0) {
            mbar_wait(sb + SM_FULL + (P_V + 2) * 8);
            const uint32_t* const ps[1] = {gx + G_ST + ((hkv * B_ + ab) * 2 + (asplit ^ (lane & 1))) * 8};
            uint4 vs[1];
            gather_n<1>(ps, vs, tag, 200);
            const int hh = (lane >> 1) & 1;
            const float ms = untag(hh ? vs[0].z : vs[0].x), ls = untag(hh ? vs[0].w : vs[0].y);
            const float mo = __shfl_xor_sync(0xffffffffu, ms, 1), lo = __shfl_xor_sync(0xffffffffu, ls, 1);
            const float m = fmaxf(ms, mo);
            const float es = exp2f(ms - m), eo = exp2f(mo - m);
            if (lane == 0 || lane == 2) stsf(sb + SM_W + hh * 4, es / (ls * es + lo * eo));
            bar_arrive(BAR_W, 32 + 256);
        }
        {
            mbar_wait(sb + SM_FULL + (OWAIT) * 8);
            const int sp = lane >> 4, d0 = (lane & 15) * 4;
            const uint32_t* base = gx + G_OP + ((ci * B_ + gw) * 2 + sp) * DH_ + d0;
            const uint32_t* const p[2] = {base, base + 64};
            uint4 v[2];
            gather_n<2>(p, v, tag, OSLEEP);
            const uint4 keep = sp ? v[1] : v[0], send = sp ? v[0] : v[1];
            const float a = untag(keep.x) + __shfl_xor_sync(0xffffffffu, untag(send.x), 16);
            const float b = untag(keep.y) + __shfl_xor_sync(0xffffffffu, untag(send.y), 16);
            const float c = untag(keep.z) + __shfl_xor_sync(0xffffffffu, untag(send.z), 16);
            const float d = untag(keep.w) + __shfl_xor_sync(0xffffffffu, untag(send.w), 16);
            const uint32_t a_ = sb + SM_O + bv_off((d0 + sp * 64) >> 1, gw);
            sts32(a_, pack_bf16(a, b));
            sts32(a_ + 8, pack_bf16(c, d));
            bar_arrive(BAR_O, 128 + 288);
            if (gw == 0) TS(12);
        }
        return;
    }

    if (warp == 0) TS(3);
    const int lrow = (lane & 7) + ((lane >> 4) << 3);
    const int lchk = (lane >> 3) & 1;
    const uint32_t off_sw = lrow * 128 + ((((warp & 3) * 2 + lchk) ^ (lane & 7)) << 4);
    const uint32_t off_ln = lrow * 288 + (warp * 2 + lchk) * 16;
    const uint32_t bv_lane = (g8 & 3) * 32 + t4 * 8;
    uint32_t* const pub_f = gx + G_FP + ((cg * 32 + ci) * B_ + 2 * t4) * 144 + warp * 16 + g8;
    uint32_t* const pub_h = gx + G_HP + ((ci * 4 + cg) * B_ + 2 * t4) * 144 + warp * 16 + g8;
    uint32_t* const pub_o = gx + G_OP + ((2 * hkv * B_ + ab) * 2 + asplit) * DH_ + warp * 16 + g8;

    if (t4 == 0 && warp < 8) st_pub4(pub_o, B_ * 2 * DH_, 0u, 0u, 0u, 0u);

    if (t4 < 2) st_pub4(pub_f, 144, 0u, 0u, 0u, 0u);
    if (warp == 0 && (lane & 6) == 0)
        st_pub(gx + G_ST + ((hkv * B_ + ab) * 2 + asplit) * 8 + (lane >> 4) * 4 + ((lane >> 3) & 1) * 2 + (lane & 1), 0u);

#pragma unroll 1
    for (int phi = 0; phi < 3; phi++) {
        const int ph = phi == 0 ? 0 : 3 - phi;
        const bool wide = ph == 2;
        if (ph == 1 && warp < 8) {
            bar_sync(BAR_Q, 128 + 256);
            uint2 qa[8];
#pragma unroll
            for (int kk = 0; kk < 8; kk++) qa[kk] = lds64(sb + SM_Q + kk * 128 + (g8 & 1) * 32 + t4 * 8);
            const int key = warp * 8 + (lane & 7);
            const uint32_t koff = key * 128;
            const uint32_t kx0 = ((lane >> 3) ^ (key & 7)) << 4, kx1 = (((lane >> 3) + 4) ^ (key & 7)) << 4;
            float mx = -INFINITY;
#pragma unroll 1
            for (int j = 0; j < 8; j++) {
                mbar_wait(sb + SM_FULL + (P_K + j) * 8);
                const uint32_t ka = sb + slot_of(P_K + j) * SLOT + koff;
                float c0[4] = {0.f, 0.f, 0.f, 0.f}, c1[4] = {0.f, 0.f, 0.f, 0.f};
#pragma unroll
                for (int qd = 0; qd < 4; qd++) {
                    uint32_t r0, r1, r2, r3;
                    ldsm_x4(ka + (qd >> 1) * 8192 + ((qd & 1) ? kx1 : kx0), r0, r1, r2, r3);
                    mma16816(c0, qa[2 * qd].x, qa[2 * qd].x, qa[2 * qd].y, qa[2 * qd].y, r0, r1);
                    mma16816(c1, qa[2 * qd + 1].x, qa[2 * qd + 1].x, qa[2 * qd + 1].y, qa[2 * qd + 1].y, r2, r3);
                }
                __syncwarp();
                if (lane == 0) mbar_arrive(sb + SM_EMPTY + (P_K + j) * 8);
                const float s0 = c0[0] + c1[0], s1 = c0[1] + c1[1];
                mx = fmaxf(mx, fmaxf(s0, s1));
                if (g8 < 2) sts64f(sb + SM_SC + (((4 * j + (warp >> 1)) * 2 + g8) * 8 + t4 * 2 + (warp & 1)) * 8, s0, s1);
            }
            if (warp == 0) TS(8);
            mx = fmaxf(mx, __shfl_xor_sync(0xffffffffu, mx, 1));
            mx = fmaxf(mx, __shfl_xor_sync(0xffffffffu, mx, 2));
            if (g8 < 2 && t4 == 0) stsf(sb + SM_RED + (warp * 2 + g8) * 4, mx);
            bar_sync(BAR_CMP, 256);
            const float kScale = 0.08838834764831845f * 1.4426950408889634f;
            const int hh = (tid >> 3) & 1;
            float m = ldsf(sb + SM_RED + ((lane & 7) * 2 + hh) * 4);
            m = fmaxf(m, __shfl_xor_sync(0xffffffffu, m, 1));
            m = fmaxf(m, __shfl_xor_sync(0xffffffffu, m, 2));
            m = fmaxf(m, __shfl_xor_sync(0xffffffffu, m, 4));
            m = untag(__float_as_uint(m * kScale));
            float l = 0.f;
#pragma unroll
            for (int n = 0; n < 2; n++) {
                const int idx = tid + n * 256;
                const uint2 s = lds64(sb + SM_SC + idx * 8);
                const float p0 = exp2f(fmaf(__uint_as_float(s.x), kScale, -m));
                const float p1 = exp2f(fmaf(__uint_as_float(s.y), kScale, -m));
                l += p0 + p1;
                sts32(sb + SM_P + ((idx >> 4) * 32 + (idx & 15)) * 4, pack_bf16(p0, p1));
            }
            l += __shfl_xor_sync(0xffffffffu, l, 1);
            l += __shfl_xor_sync(0xffffffffu, l, 2);
            l += __shfl_xor_sync(0xffffffffu, l, 4);
            l += __shfl_xor_sync(0xffffffffu, l, 16);
            if (lane < 16 && (lane & 7) == 0) stsf(sb + SM_RED + (16 + warp * 2 + hh) * 4, l);
            bar_sync(BAR_CMP, 256);
            if (warp == 0) {
                float ls = ldsf(sb + SM_RED + (16 + (lane & 7) * 2 + hh) * 4);
                ls += __shfl_xor_sync(0xffffffffu, ls, 1);
                ls += __shfl_xor_sync(0xffffffffu, ls, 2);
                ls += __shfl_xor_sync(0xffffffffu, ls, 4);
                if ((lane & 6) == 0)
                    st_pub(gx + G_ST + ((hkv * B_ + ab) * 2 + asplit) * 8 + (lane >> 4) * 4 + hh * 2 + (lane & 1),
                           tagw((lane & 1) ? ls : m, tag));
                TS(9);
            }
        }
        if (wide || warp < 8) {
            const int p0 = ph == 0 ? P_WQ : ph == 1 ? P_V : P_W1;
            const int np = ph == 1 ? 8 : 3;
            const int kpp = ph == 1 ? 4 : 3;
            const uint32_t aoff = wide ? off_ln : off_sw + (warp >> 2) * (ph == 0 ? 6144 : 8192);
            const uint32_t kstr = wide ? 16 * 288 : 16 * 128;
            uint32_t bv = sb + bv_lane + (ph == 1 ? SM_P : SM_XN);
            float acc[4] = {0.f, 0.f, 0.f, 0.f}, acd[4] = {0.f, 0.f, 0.f, 0.f};
#pragma unroll 1
            for (int p = p0; p < p0 + np; p++) {
                uint2 b[4];
#pragma unroll
                for (int ks = 0; ks < 4; ks++) b[ks] = lds64(bv + ks * 128);
                mbar_wait(sb + SM_FULL + p * 8);
                const uint32_t aa = sb + slot_of(p) * SLOT + aoff;
                uint32_t a[4][4];
#pragma unroll
                for (int ks = 0; ks < 4; ks++)
                    if (ks < 3 || kpp == 4) ldsm_x4_t(aa + ks * kstr, a[ks][0], a[ks][1], a[ks][2], a[ks][3]);
                mma16816(acc, a[0][0], a[0][1], a[0][2], a[0][3], b[0].x, b[0].y);
                mma16816(acd, a[1][0], a[1][1], a[1][2], a[1][3], b[1].x, b[1].y);
                mma16816(acc, a[2][0], a[2][1], a[2][2], a[2][3], b[2].x, b[2].y);
                if (kpp == 4) mma16816(acd, a[3][0], a[3][1], a[3][2], a[3][3], b[3].x, b[3].y);
                bv += kpp * 128;
                __syncwarp();
                if (lane == 0 && p < NEMPTY) mbar_arrive(sb + SM_EMPTY + p * 8);
                if (ph == 1 && p == p0 + np - 2) bar_sync(BAR_W, 32 + 256);
            }
            float w0 = 1.f, w1 = 1.f;
            if (ph == 1) { w0 = ldsf(sb + SM_W); w1 = ldsf(sb + SM_W + 4); }
            uint32_t* d0 = ph == 0 ? gx + G_QP + ((ci * 4 + cg) * B_ + 2 * t4) * DH_ + warp * 16 + g8
                         : ph == 1 ? pub_o : pub_h;
            if (t4 < (ph == 1 ? 1 : 2))
                st_pub4(d0, ph == 0 ? DH_ : ph == 1 ? B_ * 2 * DH_ : 144, tagw((acc[0] + acd[0]) * w0, tag),
                        tagw((acc[1] + acd[1]) * w1, tag), tagw((acc[2] + acd[2]) * w0, tag),
                        tagw((acc[3] + acd[3]) * w1, tag));
        }
        if (warp == 0) TS(ph == 0 ? 4 : ph == 1 ? 10 : 5);
    }

    {
        float c0[4] = {0.f, 0.f, 0.f, 0.f}, c1[4] = {0.f, 0.f, 0.f, 0.f};
        bar_sync(BAR_ACT, 128 + 288);
#pragma unroll
        for (int p = 0; p < 3; p++) {
            mbar_wait(sb + SM_FULL + (P_W2 + p) * 8);
#pragma unroll
            for (int ks = 0; ks < 3; ks++) {
                uint32_t a0, a1, a2, a3;
                ldsm_x4_t(sb + slot_of(P_W2 + p) * SLOT + off_ln + ks * 16 * 288, a0, a1, a2, a3);
                const uint2 b = lds64(sb + bv_lane + SM_ACT + (p * 3 + ks) * 128);
                if (ks & 1) mma16816(c1, a0, a1, a2, a3, b.x, b.y);
                else mma16816(c0, a0, a1, a2, a3, b.x, b.y);
            }
        }
        if (warp == 0) TS(11);
        uint32_t a[6][4];
#pragma unroll
        for (int p = 0; p < 3; p++) {
            mbar_wait(sb + SM_FULL + (P_WO + p) * 8);
#pragma unroll
            for (int ks = 0; ks < 2; ks++)
                ldsm_x4_t(sb + slot_of(P_WO + p) * SLOT + off_ln + ks * 16 * 288,
                          a[2 * p + ks][0], a[2 * p + ks][1], a[2 * p + ks][2], a[2 * p + ks][3]);
        }
        if (warp == 0) TS(17);
        bar_sync(BAR_O, 128 + 288);
        uint2 b[8];
#pragma unroll
        for (int k = 0; k < 8; k++) b[k] = lds64(sb + bv_lane + SM_O + k * 128);
#pragma unroll
        for (int k = 0; k < 6; k++) {
            if (k & 1) mma16816(c1, a[k][0], a[k][1], a[k][2], a[k][3], b[k].x, b[k].y);
            else mma16816(c0, a[k][0], a[k][1], a[k][2], a[k][3], b[k].x, b[k].y);
        }
        if (warp == 0) TS(16);
        mbar_wait(sb + SM_FULL + (P_WO + 3) * 8);
        if (warp == 0) TS(20);
        ldsm_x4_t(sb + slot_of(P_WO + 3) * SLOT + off_ln, a[0][0], a[0][1], a[0][2], a[0][3]);
        ldsm_x4_t(sb + slot_of(P_WO + 3) * SLOT + off_ln + 16 * 288, a[1][0], a[1][1], a[1][2], a[1][3]);
        mma16816(c0, a[0][0], a[0][1], a[0][2], a[0][3], b[6].x, b[6].y);
        mma16816(c1, a[1][0], a[1][1], a[1][2], a[1][3], b[7].x, b[7].y);
        if (t4 < 2)
            st_pub4(pub_f, 144, tagw(c0[0] + c1[0], tag), tagw(c0[1] + c1[1], tag), tagw(c0[2] + c1[2], tag),
                    tagw(c0[3] + c1[3], tag));
        __syncwarp();
        if (lane == 0) mbar_arrive(sb + SM_DONE);
        if (warp == 0) TS(13);
        TS(21 + warp);
    }
}

typedef CUresult (*EncodeTiledFn)(CUtensorMap*, CUtensorMapDataType, cuuint32_t, void*, const cuuint64_t*,
                                  const cuuint64_t*, const cuuint32_t*, const cuuint32_t*, CUtensorMapInterleave,
                                  CUtensorMapSwizzle, CUtensorMapL2promotion, CUtensorMapFloatOOBfill);

void make_map_lin(EncodeTiledFn fn, CUtensorMap* tm, const void* ptr, uint64_t cols, uint64_t rows, uint32_t box_rows) {
    cuuint64_t gdim[3] = {cols, rows, 1};
    cuuint64_t gstr[2] = {cols * 2, cols * rows * 2};
    cuuint32_t box[3] = {144, box_rows, 1};
    cuuint32_t estr[3] = {1, 1, 1};
    fn(tm, CU_TENSOR_MAP_DATA_TYPE_BFLOAT16, 3, const_cast<void*>(ptr), gdim, gstr, box, estr,
       CU_TENSOR_MAP_INTERLEAVE_NONE, CU_TENSOR_MAP_SWIZZLE_NONE, CU_TENSOR_MAP_L2_PROMOTION_L2_256B,
       CU_TENSOR_MAP_FLOAT_OOB_FILL_NONE);
}
void make_map_sw(EncodeTiledFn fn, CUtensorMap* tm, const void* ptr, uint64_t cols, uint64_t rows, uint32_t box_rows) {
    cuuint64_t gdim[3] = {64, rows, cols / 64};
    cuuint64_t gstr[2] = {cols * 2, 128};
    cuuint32_t box[3] = {64, box_rows, 2};
    cuuint32_t estr[3] = {1, 1, 1};
    fn(tm, CU_TENSOR_MAP_DATA_TYPE_BFLOAT16, 3, const_cast<void*>(ptr), gdim, gstr, box, estr,
       CU_TENSOR_MAP_INTERLEAVE_NONE, CU_TENSOR_MAP_SWIZZLE_128B, CU_TENSOR_MAP_L2_PROMOTION_L2_256B,
       CU_TENSOR_MAP_FLOAT_OOB_FILL_NONE);
}

}

extern "C" void kernel_launch(void* const* d_in, const int* in_sizes, int n_in, void* d_out, int out_size) {
    (void)in_sizes; (void)n_in; (void)out_size;
    static EncodeTiledFn encode = nullptr;
    if (!encode) {
        void* fn = nullptr;
        cudaDriverEntryPointQueryResult st;
        cudaGetDriverEntryPoint("cuTensorMapEncodeTiled", &fn, cudaEnableDefault, &st);
        encode = (EncodeTiledFn)fn;
        cudaFuncSetAttribute(fused_decode_kernel, cudaFuncAttributeMaxDynamicSharedMemorySize, SMEM_BYTES);
    }
    Maps maps;
    make_map_sw(encode, &maps.m[0], d_in[3], HQ_ * DH_, D_, 48);
    make_map_sw(encode, &maps.m[1], d_in[1], DH_, (uint64_t)B_ * HKV_ * SK_, 64);
    make_map_sw(encode, &maps.m[2], d_in[2], DH_, (uint64_t)B_ * HKV_ * SK_, 64);
    make_map_lin(encode, &maps.m[3], d_in[6], F_, D_, 48);
    make_map_lin(encode, &maps.m[4], d_in[8], D_, F_, 48);
    make_map_lin(encode, &maps.m[5], d_in[4], D_, HQ_ * DH_, 32);
    fused_decode_kernel<<<NCTA, NTHREADS, SMEM_BYTES>>>(maps, (const __nv_bfloat16*)d_in[0],
                                                        (const __nv_bfloat16*)d_in[7], (__nv_bfloat16*)d_out);
}
```

```cpp
#include <cuda_runtime.h>
#include <cuda_bf16.h>
#include <cuda.h>
#include <stdint.h>

namespace {

constexpr int D_ = 576, HQ_ = 32, HKV_ = 16, SK_ = 4096, DH_ = 128, W_ = 1024, F_ = 4608, B_ = 4;
constexpr int NCTA = 128;
constexpr int PROD_WARP = 17;
constexpr int NTHREADS = 576;
constexpr int DMIN = 2, DMAX = 6;
constexpr int NCP = 2;
constexpr int NFIRST = 4;
constexpr float PRATE = 25.25f;
constexpr float PW0 = 26.f;
constexpr float PW1 = 36.f;
constexpr int QSW = 25;
constexpr float PT0 = 200.f;
constexpr unsigned OSLEEP = 200, FSLEEP = 200;
constexpr int SLOT = 16384;
constexpr int NSLOT = 13;
constexpr int P_WQ = 0, P_W1 = 3, P_K = 6, P_V = 14, P_W2 = 22, P_WO = 25, NPIECE = 29;
constexpr int NEMPTY = NPIECE - NSLOT;

constexpr int SM_XN = NSLOT * SLOT;
constexpr int SM_ACT = SM_XN + 9 * 128;
constexpr int SM_O = SM_ACT + 9 * 128;
constexpr int SM_Q = SM_O + 8 * 128;
constexpr int SM_P = SM_Q + 8 * 128;
constexpr int SM_SC = SM_P + 32 * 128;
constexpr int SM_X = SM_SC + 512 * 8;
constexpr int SM_B1 = SM_X + 4 * 144 * 4;
constexpr int SM_HS = SM_B1 + 144 * 4;
constexpr int SM_RED = SM_HS + 4 * 144 * 4;
constexpr int SM_W = SM_RED + 32 * 4;
constexpr int SM_FULL = SM_W + 8;
constexpr int SM_EMPTY = SM_FULL + NPIECE * 8;
constexpr int SM_DONE = SM_EMPTY + NEMPTY * 8;
constexpr int SM_TAG = SM_DONE + 8;
constexpr int SM_TOTAL = SM_TAG + 16;
constexpr int SMEM_BYTES = SM_TOTAL + 1024;

constexpr unsigned SPIN_LIMIT = 1u << 21;

constexpr int BAR_CMP = 1;
constexpr int BAR_Q = 2;
constexpr int BAR_ACT = 3;
constexpr int BAR_O = 4;
constexpr int BAR_INIT = 5;
constexpr int BAR_G = 6;
constexpr int BAR_W = 7;

constexpr int G_QP = 0;
constexpr int G_HP = G_QP + HQ_ * 4 * B_ * DH_;
constexpr int G_OP = G_HP + 32 * 4 * B_ * 144;
constexpr int G_ST = G_OP + HQ_ * B_ * 2 * DH_;
constexpr int G_FP = G_ST + HKV_ * B_ * 2 * 8;
constexpr int G_EPOCH = G_FP + 4 * 32 * B_ * 144;
__device__ __align__(256) uint32_t g_x[G_EPOCH + 64];


__device__ __forceinline__ uint32_t smem_u32(const void* p) { return (uint32_t)__cvta_generic_to_shared(p); }
__device__ __forceinline__ void mbar_init(uint32_t bar, uint32_t cnt) {
    asm volatile("mbarrier.init.shared::cta.b64 [%0], %1;" ::"r"(bar), "r"(cnt) : "memory");
}
__device__ __forceinline__ void mbar_expect_tx(uint32_t bar, uint32_t bytes) {
    asm volatile("mbarrier.arrive.expect_tx.shared::cta.b64 _, [%0], %1;" ::"r"(bar), "r"(bytes) : "memory");
}
__device__ __forceinline__ void mbar_arrive(uint32_t bar) {
    asm volatile("mbarrier.arrive.shared::cta.b64 _, [%0];" ::"r"(bar) : "memory");
}
__device__ __forceinline__ bool mbar_test(uint32_t bar) {
    uint32_t ok;
    asm volatile(
        "{\n.reg .pred p;\n"
        "mbarrier.test_wait.parity.shared::cta.b64 p, [%1], 0;\n"
        "selp.u32 %0, 1, 0, p;\n}"
        : "=r"(ok) : "r"(bar) : "memory");
    return ok != 0;
}
__device__ __forceinline__ void mbar_wait(uint32_t bar) {
    asm volatile(
        "{\n.reg .pred p;\n.reg .u32 c;\n"
        "mov.u32 c, 0;\n"
        "W_%=:\n"
        "mbarrier.try_wait.parity.shared::cta.b64 p, [%0], 0;\n"
        "@p bra D_%=;\n"
        "add.u32 c, c, 1;\n"
        "setp.lt.u32 p, c, %1;\n"
        "@p bra W_%=;\n"
        "D_%=:\n}"
        ::"r"(bar), "n"(SPIN_LIMIT) : "memory");
}
__device__ __forceinline__ void tma_3d(uint32_t dst, const CUtensorMap* tm, int c0, int c1, int c2, uint32_t bar) {
    uint64_t pol;
    asm volatile("createpolicy.fractional.L2::evict_first.b64 %0, 1.0;" : "=l"(pol));
    asm volatile(
        "cp.async.bulk.tensor.3d.shared::cluster.global.mbarrier::complete_tx::bytes.L2::cache_hint"
        " [%0], [%1, {%3, %4, %5}], [%2], %6;"
        ::"r"(dst), "l"(tm), "r"(bar), "r"(c0), "r"(c1), "r"(c2), "l"(pol) : "memory");
}
__device__ __forceinline__ void prefetch_tm(const CUtensorMap* tm) {
    asm volatile("prefetch.tensormap [%0];" ::"l"(tm) : "memory");
}
__device__ __forceinline__ void ldsm_x4(uint32_t addr, uint32_t& r0, uint32_t& r1, uint32_t& r2, uint32_t& r3) {
    asm volatile("ldmatrix.sync.aligned.m8n8.x4.shared.b16 {%0,%1,%2,%3}, [%4];"
                 : "=r"(r0), "=r"(r1), "=r"(r2), "=r"(r3) : "r"(addr) : "memory");
}
__device__ __forceinline__ void ldsm_x4_t(uint32_t addr, uint32_t& r0, uint32_t& r1, uint32_t& r2, uint32_t& r3) {
    asm volatile("ldmatrix.sync.aligned.m8n8.x4.trans.shared.b16 {%0,%1,%2,%3}, [%4];"
                 : "=r"(r0), "=r"(r1), "=r"(r2), "=r"(r3) : "r"(addr) : "memory");
}
__device__ __forceinline__ void mma16816(float (&c)[4], uint32_t a0, uint32_t a1, uint32_t a2, uint32_t a3,
                                         uint32_t b0, uint32_t b1) {
    asm volatile(
        "mma.sync.aligned.m16n8k16.row.col.f32.bf16.bf16.f32 {%0,%1,%2,%3}, {%4,%5,%6,%7}, {%8,%9}, {%0,%1,%2,%3};"
        : "+f"(c[0]), "+f"(c[1]), "+f"(c[2]), "+f"(c[3])
        : "r"(a0), "r"(a1), "r"(a2), "r"(a3), "r"(b0), "r"(b1));
}
__device__ __forceinline__ void bar_sync(int id, int nthreads) {
    asm volatile("bar.sync %0, %1;" ::"r"(id), "r"(nthreads) : "memory");
}
__device__ __forceinline__ void bar_arrive(int id, int nthreads) {
    asm volatile("bar.arrive %0, %1;" ::"r"(id), "r"(nthreads) : "memory");
}
__device__ __forceinline__ uint2 lds64(uint32_t a) {
    uint2 v; asm volatile("ld.shared.v2.u32 {%0,%1}, [%2];" : "=r"(v.x), "=r"(v.y) : "r"(a) : "memory"); return v;
}
__device__ __forceinline__ float ldsf(uint32_t a) {
    float v; asm volatile("ld.shared.f32 %0, [%1];" : "=f"(v) : "r"(a) : "memory"); return v;
}
__device__ __forceinline__ void sts32(uint32_t a, uint32_t v) {
    asm volatile("st.shared.u32 [%0], %1;" ::"r"(a), "r"(v) : "memory");
}
__device__ __forceinline__ void stsf(uint32_t a, float v) {
    asm volatile("st.shared.f32 [%0], %1;" ::"r"(a), "f"(v) : "memory");
}
__device__ __forceinline__ void sts64f(uint32_t a, float v0, float v1) {
    asm volatile("st.shared.v2.f32 [%0], {%1,%2};" ::"r"(a), "f"(v0), "f"(v1) : "memory");
}
__device__ __forceinline__ void sts16(uint32_t a, __nv_bfloat16 v) {
    asm volatile("st.shared.u16 [%0], %1;" ::"r"(a), "h"(__bfloat16_as_ushort(v)) : "memory");
}
__device__ __forceinline__ uint32_t tagw(float v, uint32_t tag) { return (__float_as_uint(v) & ~15u) | tag; }
__device__ __forceinline__ void st_pub(uint32_t* p, uint32_t v) {
    asm volatile("st.relaxed.gpu.global.u32 [%0], %1;" ::"l"(p), "r"(v) : "memory");
}
__device__ __forceinline__ void st_pub4(uint32_t* d0, int S, uint32_t w0, uint32_t w1, uint32_t w2, uint32_t w3, int C = 8) {
    st_pub(d0, w0); st_pub(d0 + S, w1); st_pub(d0 + C, w2); st_pub(d0 + S + C, w3);
}
__device__ __forceinline__ uint4 ld_poll(const uint32_t* p) {
    uint4 v;
    asm volatile("ld.relaxed.gpu.global.v4.u32 {%0,%1,%2,%3}, [%4];"
                 : "=r"(v.x), "=r"(v.y), "=r"(v.z), "=r"(v.w) : "l"(p) : "memory");
    return v;
}
__device__ __forceinline__ bool tag_ok(const uint4& v, uint32_t tag) {
    return ((((v.x ^ tag) | (v.y ^ tag)) | ((v.z ^ tag) | (v.w ^ tag))) & 15u) == 0;
}
template <int N>
__device__ __forceinline__ void gather_n(const uint32_t* const (&p)[N], uint4 (&v)[N], uint32_t tag, unsigned sleep_ns) {
#pragma unroll
    for (int n = 0; n < N; n++) v[n] = make_uint4(0, 0, 0, 0);
    unsigned it = 0;
#pragma unroll 1
    while (true) {
#pragma unroll
        for (int n = 0; n < N; n++)
            if (!tag_ok(v[n], tag)) v[n] = ld_poll(p[n]);
        bool ok = true;
#pragma unroll
        for (int n = 0; n < N; n++) ok = ok && tag_ok(v[n], tag);
        if (ok || ++it > SPIN_LIMIT) break;
        __nanosleep(sleep_ns);
    }
    __syncwarp();
}
__device__ __forceinline__ float untag(uint32_t w) { return __uint_as_float(w & ~15u); }
__device__ __forceinline__ float bf16r(float v) { return __bfloat162float(__float2bfloat16_rn(v)); }
__device__ __forceinline__ uint32_t pack_bf16(float lo, float hi) {
    __nv_bfloat162 h = __floats2bfloat162_rn(lo, hi);
    return *reinterpret_cast<uint32_t*>(&h);
}
__device__ __forceinline__ uint32_t bv_off(int e2, int n) {
    return ((e2 >> 3) * 32 + n * 8 + (e2 & 3) * 2 + ((e2 >> 2) & 1)) * 4;
}
__device__ __forceinline__ float mish(float h) {
    const float e = __expf(fminf(h, 30.f));
    const float n = e * (e + 2.f);
    return h * __fdividef(n, n + 2.f);
}
__device__ __forceinline__ int slot_of(int p) { return p < NSLOT ? p : (p < 2 * NSLOT ? p - NSLOT : p - 2 * NSLOT); }

__device__ __forceinline__ void final_reduce(uint32_t sb, uint32_t* gx, __nv_bfloat16* out, int ci, int cg, int gw, int lane,
                                             uint32_t tag, bool bump_epoch) {
    const int task = ci + 32 * gw;
    if (task >= 72) return;
    const int tb = task / 18, tc = (task % 18) * 8;
    const uint32_t* fbase = gx + G_FP + (cg * 72 + task) * 256 + lane * 4;
    const int ocol = tc + (lane & 1) * 4 + ((lane >> 4) & 1) * 2 + ((lane >> 3) & 1);
    const float xv = ldsf(sb + SM_X + (tb * 144 + ocol) * 4);
    uint4 v0 = make_uint4(0, 0, 0, 0), v1 = v0;
    mbar_wait(sb + SM_FULL + (P_WO + 2) * 8);
    unsigned it = 0;
#pragma unroll 1
    while (true) {
        if (!tag_ok(v0, tag)) v0 = ld_poll(fbase);
        if (!tag_ok(v1, tag)) v1 = ld_poll(fbase + 128);
        if ((tag_ok(v0, tag) && tag_ok(v1, tag)) || ++it > SPIN_LIMIT) break;
        if (!mbar_test(sb + SM_DONE)) __nanosleep(FSLEEP);
    }
    __syncwarp();
    const float r0 = untag(v0.x) + untag(v1.x), r1 = untag(v0.y) + untag(v1.y);
    const float r2 = untag(v0.z) + untag(v1.z), r3 = untag(v0.w) + untag(v1.w);
    const bool u16 = lane & 16, u8 = lane & 8;
    const float sa = (u16 ? r2 : r0) + __shfl_xor_sync(0xffffffffu, u16 ? r0 : r2, 16);
    const float sc = (u16 ? r3 : r1) + __shfl_xor_sync(0xffffffffu, u16 ? r1 : r3, 16);
    float s1 = (u8 ? sc : sa) + __shfl_xor_sync(0xffffffffu, u8 ? sa : sc, 8);
    s1 += __shfl_xor_sync(0xffffffffu, s1, 4);
    s1 += __shfl_xor_sync(0xffffffffu, s1, 2);
    if ((lane & 6) == 0) out[tb * D_ + cg * 144 + ocol] = __float2bfloat16_rn(xv + s1);
    if (bump_epoch && lane == 0) {
        st_pub(gx + G_EPOCH, tag % 15u);
    }
}

struct Maps { CUtensorMap m[6]; };

__global__ void __launch_bounds__(NTHREADS, 1)
fused_decode_kernel(const __grid_constant__ Maps maps, const __nv_bfloat16* __restrict__ x,
                    const __nv_bfloat16* __restrict__ b1, __nv_bfloat16* __restrict__ out,
                    const __nv_bfloat16* __restrict__ wq) {
    extern __shared__ unsigned char smem_raw[];
    const uint32_t sb = (smem_u32(smem_raw) + 1023u) & ~1023u;

    const int tid = threadIdx.x, warp = tid >> 5, lane = tid & 31;
    const int cta = blockIdx.x;
    const int ci = cta >> 2, cg = cta & 3;
    const int hkv = ci >> 1;
    const int bs = ((ci & 1) << 2) | cg;
    const int ab = bs >> 1, asplit = bs & 1;
    const int kv_row0 = (ab * HKV_ + hkv) * SK_ + (SK_ - W_) + asplit * 512;

    if (warp >= 5 && warp < 13) {
        const int t = tid - 160;
        uint64_t pol;
        asm volatile("createpolicy.fractional.L2::evict_first.b64 %0, 1.0;" : "=l"(pol));
        const char* src = reinterpret_cast<const char*>(wq + (size_t)(cg * 144 + (t >> 4)) * (HQ_ * DH_) + ci * 128) + (t & 15) * 16;
        const uint32_t dst = sb + (t >> 4) * 128 + ((t >> 3) & 1) * 6144 + (((t & 7) ^ ((t >> 4) & 7)) << 4);
#pragma unroll
        for (int j = 0; j < 3 * NCP; j++)
            asm volatile("cp.async.cg.shared.global.L2::cache_hint [%0], [%1], 16, %2;"
                         ::"r"(dst + (j / 3) * SLOT + (j % 3) * 16 * 128), "l"(src + (size_t)j * 16 * (HQ_ * DH_ * 2)), "l"(pol)
                         : "memory");
    }
    unsigned t_start = 0;
    if (tid == PROD_WARP * 32) {
        mbar_init(sb + SM_FULL + 2 * 8, 1);
        mbar_init(sb + SM_FULL + 3 * 8, 1);
        asm volatile("fence.mbarrier_init.release.cluster;" ::: "memory");
        mbar_expect_tx(sb + SM_FULL + 2 * 8, 48 * 256);
        tma_3d(sb + 2 * SLOT, &maps.m[0], 0, cg * 144 + 2 * 48, 2 * ci, sb + SM_FULL + 2 * 8);
        mbar_expect_tx(sb + SM_FULL + 3 * 8, 48 * 288);
        tma_3d(sb + 3 * SLOT, &maps.m[3], ci * 144, cg * 144, 0, sb + SM_FULL + 3 * 8);
        asm volatile("mov.u32 %0, %%globaltimer_lo;" : "=r"(t_start));
    }

    if (warp == PROD_WARP) {
        const int p = lane;
        int mi, c0 = 0, c1, bytes = 48 * 288;
        float kb;
        if (p < P_K)       { mi = 3; c0 = ci * 144; c1 = cg * 144 + (p - P_W1) * 48; kb = 36.f + 13.5f * (p - P_W1); }
        else if (p < P_V)  { mi = 1; c1 = kv_row0 + (p - P_K) * 64; bytes = 16384; kb = 76.5f + 16.f * (p - P_K); }
        else if (p < P_W2) { mi = 2; c1 = kv_row0 + (p - P_V) * 64; bytes = 16384; kb = 76.5f + 16.f * (p - P_K); }
        else if (p < P_WO) { mi = 4; c0 = cg * 144; c1 = ci * 144 + (p - P_W2) * 48; kb = 332.5f + 13.5f * (p - P_W2); }
        else { mi = 5; c0 = cg * 144; c1 = ci * 128 + (p - P_WO) * 32; bytes = 32 * 288; kb = 373.f + 9.f * (p - P_WO); }
        const uint32_t fb = sb + SM_FULL + p * 8;
        if (p >= 1 && p < 6) prefetch_tm(&maps.m[p]);
        if (lane == 0) {
#pragma unroll
            for (int q = 0; q < NCP; q++) mbar_init(sb + SM_FULL + q * 8, 256);
#pragma unroll
            for (int q = NFIRST; q < NPIECE; q++) mbar_init(sb + SM_FULL + q * 8, 1);
#pragma unroll
            for (int e = 0; e <= NEMPTY; e++) mbar_init(sb + SM_EMPTY + e * 8, (e == NEMPTY || (e >= P_W1 && e < P_W1 + 3)) ? 9 : 8);
            asm volatile("fence.mbarrier_init.release.cluster;" ::: "memory");
        }
        __syncwarp();
        bar_arrive(BAR_INIT, NTHREADS);
        const unsigned t_issue = __shfl_sync(0xffffffffu, t_start, 0) + (unsigned)(int)(PT0 + (kb - (p < QSW ? PW0 : PW1)) * (1000.f / PRATE));
#pragma unroll 1
        for (int q = NFIRST; q < NPIECE; q++) {
            if (lane == q) {
                if (q - DMAX >= NCP) mbar_wait(fb - DMAX * 8);
                unsigned it = 0;
                while (!mbar_test(fb - DMIN * 8) && ++it < SPIN_LIMIT) {
                    unsigned now;
                    asm volatile("mov.u32 %0, %%globaltimer_lo;" : "=r"(now));
                    if ((int)(now - t_issue) >= 0) break;
                }
                if (q >= NSLOT) mbar_wait(sb + SM_EMPTY + (q - NSLOT) * 8);
                mbar_expect_tx(fb, bytes);
                tma_3d(sb + slot_of(p) * SLOT, &maps.m[mi], c0, c1, 0, fb);
            }
            __syncwarp();
        }
        return;
    }

    const int g8 = lane >> 2, t4 = lane & 3;
    uint32_t* const gx = g_x;

    if (warp < 4) {
        const uint32_t* xw = reinterpret_cast<const uint32_t*>(x + warp * D_);
        uint32_t w[9];
#pragma unroll
        for (int j = 0; j < 9; j++) w[j] = __ldg(xw + lane + 32 * j);
        uint32_t us[3];
#pragma unroll
        for (int j = 0; j < 3; j++) us[j] = __ldg(xw + cg * 72 + min(lane + 32 * j, 71));
        float s = 0.f;
#pragma unroll
        for (int j = 0; j < 9; j++) s += __uint_as_float(w[j] << 16) + __uint_as_float(w[j] & 0xffff0000u);
#pragma unroll
        for (int o = 16; o > 0; o >>= 1) s += __shfl_xor_sync(0xffffffffu, s, o);
        const float mean = s * (1.0f / D_);
        float q = 0.f;
#pragma unroll
        for (int j = 0; j < 9; j++) {
            const float d0 = __uint_as_float(w[j] << 16) - mean, d1 = __uint_as_float(w[j] & 0xffff0000u) - mean;
            q += d0 * d0 + d1 * d1;
        }
#pragma unroll
        for (int o = 16; o > 0; o >>= 1) q += __shfl_xor_sync(0xffffffffu, q, o);
        const float mb = bf16r(mean);
        const float rden = __frcp_rn(bf16r(__fsqrt_rn(bf16r(bf16r(q * (1.0f / D_)) + 1e-5f))));
#pragma unroll
        for (int j = 0; j < 3; j++) {
            const int e2 = min(lane + 32 * j, 71);
            const float v0 = __uint_as_float(us[j] << 16), v1 = __uint_as_float(us[j] & 0xffff0000u);
            sts32(sb + SM_XN + bv_off(e2, warp), pack_bf16(bf16r(v0 - mb) * rden, bf16r(v1 - mb) * rden));
            sts64f(sb + SM_X + (warp * 144 + 2 * e2) * 4, v0, v1);
        }
    } else if (warp == 4) {
        if (lane == 0) {
            unsigned e;
            asm volatile("ld.relaxed.gpu.global.u32 %0, [%1];" : "=r"(e) : "l"(gx + G_EPOCH) : "memory");
            sts32(sb + SM_TAG, e);
        }
    }
    bar_sync(BAR_INIT, NTHREADS);
    if (warp >= 5 && warp < 13) {
        asm volatile("cp.async.wait_all;" ::: "memory");
#pragma unroll
        for (int q = 0; q < NCP; q++) mbar_arrive(sb + SM_FULL + q * 8);
    }
    const unsigned epoch = __float_as_uint(ldsf(sb + SM_TAG));
    const uint32_t tag = epoch % 15u + 1u;


    if (warp >= 13) {
        const int gw = warp - 13;
        {
            const int e2 = gw * 32 + lane;
            if (e2 < 72) {
                const uint32_t u = __ldg(reinterpret_cast<const uint32_t*>(b1 + ci * 144) + e2);
                sts64f(sb + SM_B1 + e2 * 8, __uint_as_float(u << 16), __uint_as_float(u & 0xffff0000u));
            }
        }
        {
            mbar_wait(sb + SM_FULL + (P_K + 7) * 8);
            const int rg = lane >> 3, j = lane & 7;
            const uint32_t* base = gx + G_HP + ((ci * 4 + rg) * B_ + gw) * 144 + j * 4;
            const uint32_t* const p[5] = {base, base + 32, base + 64, base + 96, base + (j < 4 ? 128 : 96)};
            uint4 v[5];
            gather_n<5>(p, v, tag, 300);
#pragma unroll
            for (int n = 0; n < 5; n++) {
                const bool u16 = lane & 16, u8 = lane & 8;
                const float k0 = untag(u16 ? v[n].z : v[n].x), k1 = untag(u16 ? v[n].w : v[n].y);
                const float s0 = untag(u16 ? v[n].x : v[n].z), s1 = untag(u16 ? v[n].y : v[n].w);
                const float a = k0 + __shfl_xor_sync(0xffffffffu, s0, 16);
                const float b = k1 + __shfl_xor_sync(0xffffffffu, s1, 16);
                const float h = (u8 ? b : a) + __shfl_xor_sync(0xffffffffu, u8 ? a : b, 8);
                stsf(sb + SM_HS + (gw * 144 + ((n == 4 && j >= 4) ? 96 : n * 32) + j * 4 + rg) * 4, h);
            }
            bar_sync(BAR_G, 128);
#pragma unroll 1
            for (int f = lane; f < 144; f += 32)
                sts16(sb + SM_ACT + bv_off(f >> 1, gw) + (f & 1) * 2,
                      __float2bfloat16_rn(mish(ldsf(sb + SM_HS + (gw * 144 + f) * 4) + ldsf(sb + SM_B1 + f * 4))));
            bar_arrive(BAR_ACT, 128 + 288);
        }
        final_reduce(sb, gx, out, ci, cg, gw, lane, tag, cta == 0 && gw == 0);
        return;
    }

    if (warp >= 9) {
        const int gw = warp - 9;
        {
            mbar_wait(sb + SM_FULL + (P_K + 2) * 8);
            const int hh = gw >> 1, rg = lane >> 3, q0 = (gw & 1) * 64 + (lane & 7) * 4;
            const uint32_t* qbase = gx + G_QP + (((2 * hkv + hh) * 4 + rg) * B_ + ab) * DH_ + q0;
            const uint32_t* const pq[2] = {qbase, qbase + 32};
            uint4 vq[2];
            gather_n<2>(pq, vq, tag, 200);
#pragma unroll
            for (int n = 0; n < 2; n++) {
                float a = untag(vq[n].x), b = untag(vq[n].y), c = untag(vq[n].z), d = untag(vq[n].w);
#pragma unroll
                for (int o = 8; o <= 16; o <<= 1) {
                    a += __shfl_xor_sync(0xffffffffu, a, o);
                    b += __shfl_xor_sync(0xffffffffu, b, o);
                    c += __shfl_xor_sync(0xffffffffu, c, o);
                    d += __shfl_xor_sync(0xffffffffu, d, o);
                }
                if (rg == 0) {
                    const uint32_t a_ = sb + SM_Q + bv_off((q0 + n * 32) >> 1, hh);
                    sts32(a_, pack_bf16(a, b));
                    sts32(a_ + 8, pack_bf16(c, d));
                }
            }
            bar_arrive(BAR_Q, 128 + 256);
        }
        if (gw == 0) {
            mbar_wait(sb + SM_FULL + (P_V + 2) * 8);
            const uint32_t* const ps[1] = {gx + G_ST + ((hkv * B_ + ab) * 2 + (asplit ^ (lane & 1))) * 8};
            uint4 vs[1];
            gather_n<1>(ps, vs, tag, 200);
            const int hh = (lane >> 1) & 1;
            const float ms = untag(hh ? vs[0].z : vs[0].x), ls = untag(hh ? vs[0].w : vs[0].y);
            const float mo = __shfl_xor_sync(0xffffffffu, ms, 1), lo = __shfl_xor_sync(0xffffffffu, ls, 1);
            const float m = fmaxf(ms, mo);
            const float es = exp2f(ms - m), eo = exp2f(mo - m);
            if (lane == 0 || lane == 2) stsf(sb + SM_W + hh * 4, es / (ls * es + lo * eo));
            bar_arrive(BAR_W, 32 + 256);
        }
        {
            mbar_wait(sb + SM_FULL + (P_W2 + 2) * 8);
            const int sp = lane >> 4, d0 = (lane & 15) * 4;
            const uint32_t* base = gx + G_OP + ((ci * B_ + gw) * 2 + sp) * DH_ + d0;
            const uint32_t* const p[2] = {base, base + 64};
            uint4 v[2];
            gather_n<2>(p, v, tag, OSLEEP);
            const uint4 keep = sp ? v[1] : v[0], send = sp ? v[0] : v[1];
            const float a = untag(keep.x) + __shfl_xor_sync(0xffffffffu, untag(send.x), 16);
            const float b = untag(keep.y) + __shfl_xor_sync(0xffffffffu, untag(send.y), 16);
            const float c = untag(keep.z) + __shfl_xor_sync(0xffffffffu, untag(send.z), 16);
            const float d = untag(keep.w) + __shfl_xor_sync(0xffffffffu, untag(send.w), 16);
            const uint32_t a_ = sb + SM_O + bv_off((d0 + sp * 64) >> 1, gw);
            sts32(a_, pack_bf16(a, b));
            sts32(a_ + 8, pack_bf16(c, d));
            bar_arrive(BAR_O, 128 + 288);
        }
        return;
    }

    const int lrow = (lane & 7) + ((lane >> 4) << 3);
    const int lchk = (lane >> 3) & 1;
    const uint32_t off_sw = lrow * 128 + ((((warp & 3) * 2 + lchk) ^ (lane & 7)) << 4);
    const uint32_t off_ln = lrow * 288 + (warp * 2 + lchk) * 16;
    const uint32_t bv_lane = (g8 & 3) * 32 + t4 * 8;
    uint32_t* const pub_f = gx + G_FP + ((cg * 72 + 2 * t4 * 18 + 2 * warp) * 32 + ci) * 8 + g8;
    uint32_t* const pub_h = gx + G_HP + ((ci * 4 + cg) * B_ + 2 * t4) * 144 + warp * 16 + g8;
    uint32_t* const pub_o = gx + G_OP + ((2 * hkv * B_ + ab) * 2 + asplit) * DH_ + warp * 16 + g8;

    if (t4 == 0 && warp < 8) st_pub4(pub_o, B_ * 2 * DH_, 0u, 0u, 0u, 0u);

    if (t4 < 2) st_pub4(pub_f, 18 * 256, 0u, 0u, 0u, 0u, 256);
    if (warp == 0 && (lane & 6) == 0)
        st_pub(gx + G_ST + ((hkv * B_ + ab) * 2 + asplit) * 8 + (lane >> 4) * 4 + ((lane >> 3) & 1) * 2 + (lane & 1), 0u);

#pragma unroll 1
    for (int phi = 0; phi < 3; phi++) {
        const int ph = phi == 0 ? 0 : 3 - phi;
        const bool wide = ph == 2;
        if (ph == 1 && warp < 8) {
            bar_sync(BAR_Q, 128 + 256);
            uint2 qa[8];
#pragma unroll
            for (int kk = 0; kk < 8; kk++) qa[kk] = lds64(sb + SM_Q + kk * 128 + (g8 & 1) * 32 + t4 * 8);
            const int key = warp * 8 + (lane & 7);
            const uint32_t koff = key * 128;
            const uint32_t kx0 = ((lane >> 3) ^ (key & 7)) << 4, kx1 = (((lane >> 3) + 4) ^ (key & 7)) << 4;
            float mx = -INFINITY;
#pragma unroll 1
            for (int j = 0; j < 8; j++) {
                mbar_wait(sb + SM_FULL + (P_K + j) * 8);
                const uint32_t ka = sb + slot_of(P_K + j) * SLOT + koff;
                float c0[4] = {0.f, 0.f, 0.f, 0.f}, c1[4] = {0.f, 0.f, 0.f, 0.f};
#pragma unroll
                for (int qd = 0; qd < 4; qd++) {
                    uint32_t r0, r1, r2, r3;
                    ldsm_x4(ka + (qd >> 1) * 8192 + ((qd & 1) ? kx1 : kx0), r0, r1, r2, r3);
                    mma16816(c0, qa[2 * qd].x, qa[2 * qd].x, qa[2 * qd].y, qa[2 * qd].y, r0, r1);
                    mma16816(c1, qa[2 * qd + 1].x, qa[2 * qd + 1].x, qa[2 * qd + 1].y, qa[2 * qd + 1].y, r2, r3);
                }
                __syncwarp();
                if (lane == 0) mbar_arrive(sb + SM_EMPTY + (P_K + j) * 8);
                const float s0 = c0[0] + c1[0], s1 = c0[1] + c1[1];
                mx = fmaxf(mx, fmaxf(s0, s1));
                if (g8 < 2) sts64f(sb + SM_SC + (((4 * j + (warp >> 1)) * 2 + g8) * 8 + t4 * 2 + (warp & 1)) * 8, s0, s1);
            }
            mx = fmaxf(mx, __shfl_xor_sync(0xffffffffu, mx, 1));
            mx = fmaxf(mx, __shfl_xor_sync(0xffffffffu, mx, 2));
            if (g8 < 2 && t4 == 0) stsf(sb + SM_RED + (warp * 2 + g8) * 4, mx);
            bar_sync(BAR_CMP, 256);
            const float kScale = 0.08838834764831845f * 1.4426950408889634f;
            const int hh = (tid >> 3) & 1;
            float m = ldsf(sb + SM_RED + ((lane & 7) * 2 + hh) * 4);
            m = fmaxf(m, __shfl_xor_sync(0xffffffffu, m, 1));
            m = fmaxf(m, __shfl_xor_sync(0xffffffffu, m, 2));
            m = fmaxf(m, __shfl_xor_sync(0xffffffffu, m, 4));
            m = untag(__float_as_uint(m * kScale));
            float l = 0.f;
#pragma unroll
            for (int n = 0; n < 2; n++) {
                const int idx = tid + n * 256;
                const uint2 s = lds64(sb + SM_SC + idx * 8);
                const float p0 = exp2f(fmaf(__uint_as_float(s.x), kScale, -m));
                const float p1 = exp2f(fmaf(__uint_as_float(s.y), kScale, -m));
                l += p0 + p1;
                sts32(sb + SM_P + ((idx >> 4) * 32 + (idx & 15)) * 4, pack_bf16(p0, p1));
            }
            l += __shfl_xor_sync(0xffffffffu, l, 1);
            l += __shfl_xor_sync(0xffffffffu, l, 2);
            l += __shfl_xor_sync(0xffffffffu, l, 4);
            l += __shfl_xor_sync(0xffffffffu, l, 16);
            if (lane < 16 && (lane & 7) == 0) stsf(sb + SM_RED + (16 + warp * 2 + hh) * 4, l);
            bar_sync(BAR_CMP, 256);
            if (warp == 0) {
                float ls = ldsf(sb + SM_RED + (16 + (lane & 7) * 2 + hh) * 4);
                ls += __shfl_xor_sync(0xffffffffu, ls, 1);
                ls += __shfl_xor_sync(0xffffffffu, ls, 2);
                ls += __shfl_xor_sync(0xffffffffu, ls, 4);
                if ((lane & 6) == 0)
                    st_pub(gx + G_ST + ((hkv * B_ + ab) * 2 + asplit) * 8 + (lane >> 4) * 4 + hh * 2 + (lane & 1),
                           tagw((lane & 1) ? ls : m, tag));
            }
        }
        if (wide || warp < 8) {
            const int p0 = ph == 0 ? P_WQ : ph == 1 ? P_V : P_W1;
            const int np = ph == 1 ? 8 : 3;
            const int kpp = ph == 1 ? 4 : 3;
            const uint32_t aoff = wide ? off_ln : off_sw + (warp >> 2) * (ph == 0 ? 6144 : 8192);
            const uint32_t kstr = wide ? 16 * 288 : 16 * 128;
            uint32_t bv = sb + bv_lane + (ph == 1 ? SM_P : SM_XN);
            float acc[4] = {0.f, 0.f, 0.f, 0.f}, acd[4] = {0.f, 0.f, 0.f, 0.f};
#pragma unroll 1
            for (int p = p0; p < p0 + np; p++) {
                uint2 b[4];
#pragma unroll
                for (int ks = 0; ks < 4; ks++) b[ks] = lds64(bv + ks * 128);
                mbar_wait(sb + SM_FULL + p * 8);
                const uint32_t aa = sb + slot_of(p) * SLOT + aoff;
                uint32_t a[4][4];
#pragma unroll
                for (int ks = 0; ks < 4; ks++)
                    if (ks < 3 || kpp == 4) ldsm_x4_t(aa + ks * kstr, a[ks][0], a[ks][1], a[ks][2], a[ks][3]);
                mma16816(acc, a[0][0], a[0][1], a[0][2], a[0][3], b[0].x, b[0].y);
                mma16816(acd, a[1][0], a[1][1], a[1][2], a[1][3], b[1].x, b[1].y);
                mma16816(acc, a[2][0], a[2][1], a[2][2], a[2][3], b[2].x, b[2].y);
                if (kpp == 4) mma16816(acd, a[3][0], a[3][1], a[3][2], a[3][3], b[3].x, b[3].y);
                bv += kpp * 128;
                __syncwarp();
                if (lane == 0 && p < NEMPTY) mbar_arrive(sb + SM_EMPTY + p * 8);
                if (ph == 1 && p == p0 + np - 2) bar_sync(BAR_W, 32 + 256);
            }
            float w0 = 1.f, w1 = 1.f;
            if (ph == 1) { w0 = ldsf(sb + SM_W); w1 = ldsf(sb + SM_W + 4); }
            uint32_t* d0 = ph == 0 ? gx + G_QP + ((ci * 4 + cg) * B_ + 2 * t4) * DH_ + warp * 16 + g8
                         : ph == 1 ? pub_o : pub_h;
            if (t4 < (ph == 1 ? 1 : 2))
                st_pub4(d0, ph == 0 ? DH_ : ph == 1 ? B_ * 2 * DH_ : 144, tagw((acc[0] + acd[0]) * w0, tag),
                        tagw((acc[1] + acd[1]) * w1, tag), tagw((acc[2] + acd[2]) * w0, tag),
                        tagw((acc[3] + acd[3]) * w1, tag));
        }
    }


    {
        float c0[4] = {0.f, 0.f, 0.f, 0.f}, c1[4] = {0.f, 0.f, 0.f, 0.f};
        bar_sync(BAR_ACT, 128 + 288);
#pragma unroll
        for (int p = 0; p < 3; p++) {
            mbar_wait(sb + SM_FULL + (P_W2 + p) * 8);
#pragma unroll
            for (int ks = 0; ks < 3; ks++) {
                uint32_t a0, a1, a2, a3;
                ldsm_x4_t(sb + slot_of(P_W2 + p) * SLOT + off_ln + ks * 16 * 288, a0, a1, a2, a3);
                const uint2 b = lds64(sb + bv_lane + SM_ACT + (p * 3 + ks) * 128);
                if (ks & 1) mma16816(c1, a0, a1, a2, a3, b.x, b.y);
                else mma16816(c0, a0, a1, a2, a3, b.x, b.y);
            }
        }
        uint32_t a[6][4];
#pragma unroll
        for (int p = 0; p < 3; p++) {
            mbar_wait(sb + SM_FULL + (P_WO + p) * 8);
#pragma unroll
            for (int ks = 0; ks < 2; ks++)
                ldsm_x4_t(sb + slot_of(P_WO + p) * SLOT + off_ln + ks * 16 * 288,
                          a[2 * p + ks][0], a[2 * p + ks][1], a[2 * p + ks][2], a[2 * p + ks][3]);
        }
        bar_sync(BAR_O, 128 + 288);
        uint2 b[8];
#pragma unroll
        for (int k = 0; k < 8; k++) b[k] = lds64(sb + bv_lane + SM_O + k * 128);
#pragma unroll
        for (int k = 0; k < 6; k++) {
            if (k & 1) mma16816(c1, a[k][0], a[k][1], a[k][2], a[k][3], b[k].x, b[k].y);
            else mma16816(c0, a[k][0], a[k][1], a[k][2], a[k][3], b[k].x, b[k].y);
        }
        mbar_wait(sb + SM_FULL + (P_WO + 3) * 8);
        ldsm_x4_t(sb + slot_of(P_WO + 3) * SLOT + off_ln, a[0][0], a[0][1], a[0][2], a[0][3]);
        ldsm_x4_t(sb + slot_of(P_WO + 3) * SLOT + off_ln + 16 * 288, a[1][0], a[1][1], a[1][2], a[1][3]);
        mma16816(c0, a[0][0], a[0][1], a[0][2], a[0][3], b[6].x, b[6].y);
        mma16816(c1, a[1][0], a[1][1], a[1][2], a[1][3], b[7].x, b[7].y);
        if (t4 < 2)
            st_pub4(pub_f, 18 * 256, tagw(c0[0] + c1[0], tag), tagw(c0[1] + c1[1], tag), tagw(c0[2] + c1[2], tag),
                    tagw(c0[3] + c1[3], tag), 256);
        __syncwarp();
        if (lane == 0) mbar_arrive(sb + SM_DONE);
    }
}

typedef CUresult (*EncodeTiledFn)(CUtensorMap*, CUtensorMapDataType, cuuint32_t, void*, const cuuint64_t*,
                                  const cuuint64_t*, const cuuint32_t*, const cuuint32_t*, CUtensorMapInterleave,
                                  CUtensorMapSwizzle, CUtensorMapL2promotion, CUtensorMapFloatOOBfill);

void make_map_lin(EncodeTiledFn fn, CUtensorMap* tm, const void* ptr, uint64_t cols, uint64_t rows, uint32_t box_rows) {
    cuuint64_t gdim[3] = {cols, rows, 1};
    cuuint64_t gstr[2] = {cols * 2, cols * rows * 2};
    cuuint32_t box[3] = {144, box_rows, 1};
    cuuint32_t estr[3] = {1, 1, 1};
    fn(tm, CU_TENSOR_MAP_DATA_TYPE_BFLOAT16, 3, const_cast<void*>(ptr), gdim, gstr, box, estr,
       CU_TENSOR_MAP_INTERLEAVE_NONE, CU_TENSOR_MAP_SWIZZLE_NONE, CU_TENSOR_MAP_L2_PROMOTION_L2_256B,
       CU_TENSOR_MAP_FLOAT_OOB_FILL_NONE);
}
void make_map_sw(EncodeTiledFn fn, CUtensorMap* tm, const void* ptr, uint64_t cols, uint64_t rows, uint32_t box_rows) {
    cuuint64_t gdim[3] = {64, rows, cols / 64};
    cuuint64_t gstr[2] = {cols * 2, 128};
    cuuint32_t box[3] = {64, box_rows, 2};
    cuuint32_t estr[3] = {1, 1, 1};
    fn(tm, CU_TENSOR_MAP_DATA_TYPE_BFLOAT16, 3, const_cast<void*>(ptr), gdim, gstr, box, estr,
       CU_TENSOR_MAP_INTERLEAVE_NONE, CU_TENSOR_MAP_SWIZZLE_128B, CU_TENSOR_MAP_L2_PROMOTION_L2_256B,
       CU_TENSOR_MAP_FLOAT_OOB_FILL_NONE);
}

}

extern "C" void kernel_launch(void* const* d_in, const int* in_sizes, int n_in, void* d_out, int out_size) {
    (void)in_sizes; (void)n_in; (void)out_size;
    static EncodeTiledFn encode = nullptr;
    if (!encode) {
        void* fn = nullptr;
        cudaDriverEntryPointQueryResult st;
        cudaGetDriverEntryPoint("cuTensorMapEncodeTiled", &fn, cudaEnableDefault, &st);
        encode = (EncodeTiledFn)fn;
        cudaFuncSetAttribute(fused_decode_kernel, cudaFuncAttributeMaxDynamicSharedMemorySize, SMEM_BYTES);
    }
    Maps maps;
    make_map_sw(encode, &maps.m[0], d_in[3], HQ_ * DH_, D_, 48);
    make_map_sw(encode, &maps.m[1], d_in[1], DH_, (uint64_t)B_ * HKV_ * SK_, 64);
    make_map_sw(encode, &maps.m[2], d_in[2], DH_, (uint64_t)B_ * HKV_ * SK_, 64);
    make_map_lin(encode, &maps.m[3], d_in[6], F_, D_, 48);
    make_map_lin(encode, &maps.m[4], d_in[8], D_, F_, 48);
    make_map_lin(encode, &maps.m[5], d_in[4], D_, HQ_ * DH_, 32);
    fused_decode_kernel<<<NCTA, NTHREADS, SMEM_BYTES>>>(maps, (const __nv_bfloat16*)d_in[0],
                                                        (const __nv_bfloat16*)d_in[7], (__nv_bfloat16*)d_out,
                                                        (const __nv_bfloat16*)d_in[3]);
}
```
